```python
import torch

def _softmax(x, axis=-1):
    return torch.softmax(x, dim=axis)

def _gelu(x):
    return torch.nn.functional.gelu(x, approximate='tanh')

def _silu(x):
    return torch.nn.functional.silu(x)

def _sigmoid(x):
    return torch.sigmoid(x)

def _layernorm(x, axis=-1, eps=1e-05):
    m = x.mean(dim=axis, keepdim=True)
    v = x.var(dim=axis, keepdim=True, unbiased=False)
    return (x - m) / torch.sqrt(v + eps)

def _scatter_add(tgt, idx, src, axis=0):
    return tgt.clone().index_add_(axis, idx, src)

def _segment_sum(src, seg, n):
    out = torch.zeros((n,) + src.shape[1:], dtype=src.dtype)
    return out.index_add_(0, seg, src)

def _pad(x, pw):
    flat = tuple((v for pair in reversed(pw) for v in pair))
    return torch.nn.functional.pad(x, flat)
kernel_name = 'adaLN_cond__sliding_block_cached__dense_activation_silu__decode'

def setup_inputs():

    _w = lambda a: (lambda t: t.to(torch.bfloat16) if t.is_floating_point() else t)(torch.as_tensor(a))

    def _A_setup():
        B, Sq, D = (1, 1, 576)
        Hq, Hkv, Sk, Dh = (32, 16, 65536, 128)
        assert Hq % Hkv == 0, (Hq, Hkv)
        return {'x': _w((lambda *s: torch.randn(*s, dtype=torch.bfloat16) * 0.05)(B, Sq, D)), 'k_cache': _w((lambda *s: torch.randn(*s, dtype=torch.bfloat16) * 3.2)(B, Hkv, Sk, Dh)), 'v_cache': _w((lambda *s: torch.randn(*s, dtype=torch.bfloat16) * 1.6)(B, Hkv, Sk, Dh)), 'wq': _w((lambda *s: torch.randn(*s, dtype=torch.bfloat16) * 3.2)(D, Hq * Dh) * D ** (-0.5)), 'wo': _w((lambda *s: torch.randn(*s, dtype=torch.bfloat16) * 1.6)(Hq * Dh, D) * (Hq * Dh) ** (-0.5))}
    _A_in = _A_setup()

    def _B_setup():
        B, S, D, F = (1, 1, 576, 4608)
        return {'x': _w((lambda *s: torch.randn(*s, dtype=torch.bfloat16) * 0.05)(B, S, D)), 'w1': _w((lambda *s: torch.randn(*s, dtype=torch.bfloat16) * 3.2)(D, F) * D ** (-0.5)), 'w2': _w((lambda *s: torch.randn(*s, dtype=torch.bfloat16) * 3.2)(F, D) * F ** (-0.5))}
    _B_in = _B_setup()
    return {'A_x': _A_in['x'], 'A_k_cache': _A_in['k_cache'], 'A_v_cache': _A_in['v_cache'], 'A_wq': _A_in['wq'], 'A_wo': _A_in['wo'], 'B_x': _B_in['x'], 'B_w1': _B_in['w1'], 'B_w2': _B_in['w2'], 'c': _w((lambda *s: torch.randn(*s, dtype=torch.bfloat16) * 0.2)(1, 576) * 8.0), 'w_mod': _w((lambda *s: torch.randn(*s, dtype=torch.bfloat16) * 0.2)(576, 6 * 576) * 576 ** (-0.5) * 8.0)}

def reference(A_x, A_k_cache, A_v_cache, A_wq, A_wo, B_x, B_w1, B_w2, c, w_mod):

    def _A_ref(x, k_cache, v_cache, wq, wo):
        B, Sq, D = x.shape
        Hq, Dh = (32, 128)
        Hkv, Sk = (k_cache.shape[1], k_cache.shape[2])
        W = min(4096, max(256, Sk // 4))
        rep = Hq // Hkv
        q = (lambda x, *d: x.permute(*d))((x @ wq).reshape(B, Sq, Hq, Dh), 0, 2, 1, 3)
        k = (lambda x, n, axis: torch.repeat_interleave(x, n, dim=axis))(k_cache[:, :, Sk - W:, :], rep, axis=1)
        v = (lambda x, n, axis: torch.repeat_interleave(x, n, dim=axis))(v_cache[:, :, Sk - W:, :], rep, axis=1)
        scores = torch.einsum('bhqd,bhkd->bhqk', q, k) * Dh ** (-0.5)
        p = _softmax(scores, axis=-1)
        o = torch.einsum('bhqk,bhkd->bhqd', p, v)
        return (lambda x, *d: x.permute(*d))(o, 0, 2, 1, 3).reshape(B, Sq, Hq * Dh) @ wo

    def _B_ref(x, w1, w2):
        h = torch.einsum('bsd,df->bsf', x, w1)
        h = _silu(h)
        out = torch.einsum('bsf,fd->bsd', h, w2)
        return out
    x = A_x
    mod = (_silu(c) @ w_mod).reshape(c.shape[0], 6, 1, -1)
    sa, ca, ga, sb, cb, gb = (mod[:, 0].clone(), mod[:, 1].clone(), mod[:, 2].clone(), mod[:, 3].clone(), mod[:, 4].clone(), mod[:, 5].clone())
    h = _layernorm(x, axis=-1) * (1 + ca) + sa
    x = x + ga * _A_ref(h, A_k_cache, A_v_cache, A_wq, A_wo)
    h = _layernorm(x, axis=-1) * (1 + cb) + sb
    x = x + gb * _B_ref(h, B_w1, B_w2)
    return x
```

```cpp
#include <cuda_runtime.h>
#include <cuda_bf16.h>
#include <cuda.h>
#include <stdint.h>

namespace {

constexpr int SK_ = 65536, WIN_ = 4096, F_ = 4608;
constexpr int CL = 6, NCL = 16, NCTA = CL * NCL, NTHREADS = 288;
constexpr int NP1 = 32;

constexpr int P_KV = 14, N_ITEMS = 14 + 44 + 6 + 9 + 9;
constexpr int BAR_CK = N_ITEMS;
constexpr int BAR_CV = BAR_CK + 22;
constexpr int BAR_DQ = BAR_CV + 22;
constexpr int BAR_DS = BAR_DQ + 1, BAR_DO = BAR_DQ + 2, BAR_DX = BAR_DQ + 3, BAR_DH = BAR_DQ + 4;
constexpr int N_BARS = BAR_DQ + 5;
__host__ __device__ constexpr int pos_a(int j) { return j + (j + 1) / 2; }
__host__ __device__ constexpr int pos_b(int j) { return 1 + 3 * j; }

constexpr int OFF_WOA = 0;
constexpr int OFF_WOB = 32768;
constexpr int OFF_W1A = 49152;
constexpr int OFF_W1B = OFF_W1A + 49152;
constexpr int OFF_W2A = OFF_W1B + 6144;
constexpr int OFF_W2B = OFF_W2A + 36864;
constexpr int OFF_M = 0;
constexpr int OFF_Q = 46080;
constexpr int OFF_X = 95232;
constexpr int OFF_SMALL = OFF_X + 14 * 8192;
constexpr int S_BARS = OFF_SMALL;
constexpr int S_H = S_BARS + 1088;
constexpr int S_X = S_H + 192;
constexpr int S_IN = S_X + 2304;
constexpr int S_QS = S_IN + 6912;
constexpr int S_P = S_QS + 512;
constexpr int S_PART = S_P + 2848;
constexpr int S_RED = S_PART + 3072;
constexpr int S_ST = S_RED + 256;
constexpr int S_F = S_ST + 96;
constexpr int S_HV = S_F + 64;
constexpr int S_G = S_HV + 576;
constexpr int S_MISC = S_G + 1536;
constexpr int SMEM_BYTES = S_MISC + 32;
static_assert(N_BARS * 8 <= 1088, "barriers");
static_assert(OFF_W2B + 18432 <= OFF_X + 8 * 8192, "late weights");
static_assert(SMEM_BYTES <= 232448, "smem");
constexpr int PROW = 712;

#define RATE_KV 3250.0f
#define RATE_LATE 3100.0f
#define WIN_KV 8
#define WIN_LATE 7
#define LATE_FROM 18
#define P1_Q_STEP 150.0f
#define DELAY_G1 1500
#define DELAY_G2 800
constexpr float BYTES_22 = 46080.f + 49152.f + 44 * 8192.f + 49152.f + 55296.f + 55296.f;
constexpr float BYTES_21 = BYTES_22 - 2 * 8192.f;
constexpr float BYTES_ALL = 2 * NCL * BYTES_22 + 4 * NCL * BYTES_21;

#define T_RATE_KV RATE_KV
#define T_RATE_LATE RATE_LATE
#define T_WIN_KV WIN_KV
#define T_WIN_LATE WIN_LATE
#define T_LATE_FROM LATE_FROM
#define T_P1_Q_STEP P1_Q_STEP
#define T_DELAY_G1 DELAY_G1
#define T_DELAY_G2 DELAY_G2

struct Maps { CUtensorMap wmod, wq, k, v, woa, wob, w1a, w1b, w2a, w2b; };
struct Ptrs {
    const __nv_bfloat16 *x, *c;
    __nv_bfloat16* out;
};

constexpr int MB_MOD = 0;
constexpr int MB_P1 = MB_MOD + NCTA * 40;
constexpr int MB_P2 = MB_P1 + NCTA * 96;
constexpr int MB_END = MB_P2 + NCTA * 96;
__device__ __align__(128) uint32_t g_mail[MB_END];
__device__ uint32_t g_count;

__device__ __forceinline__ uint32_t smem_u32(const void* p) { return (uint32_t)__cvta_generic_to_shared(p); }
__device__ __forceinline__ void mbar_init(uint32_t bar, uint32_t cnt) {
    asm volatile("mbarrier.init.shared::cta.b64 [%0], %1;" ::"r"(bar), "r"(cnt));
}
__device__ __forceinline__ void mbar_expect_tx(uint32_t bar, uint32_t bytes) {
    asm volatile("mbarrier.arrive.expect_tx.shared::cta.b64 _, [%0], %1;" ::"r"(bar), "r"(bytes) : "memory");
}
__device__ __forceinline__ void mbar_arrive(uint32_t bar) {
    asm volatile("mbarrier.arrive.shared::cta.b64 _, [%0];" ::"r"(bar) : "memory");
}
constexpr int SPIN_LIMIT = 1 << 18;
__device__ __forceinline__ uint32_t mbar_try(uint32_t bar) {
    uint32_t ok;
    asm volatile("{\n.reg .pred p;\nmbarrier.try_wait.parity.shared::cta.b64 p, [%1], 0;\nselp.u32 %0, 1, 0, p;\n}"
                 : "=r"(ok) : "r"(bar) : "memory");
    return ok;
}
__device__ __forceinline__ uint32_t mbar_test(uint32_t bar) {
    uint32_t ok;
    asm volatile("{\n.reg .pred p;\nmbarrier.test_wait.parity.shared::cta.b64 p, [%1], 0;\nselp.u32 %0, 1, 0, p;\n}"
                 : "=r"(ok) : "r"(bar) : "memory");
    return ok;
}
__device__ __forceinline__ void mbar_wait(uint32_t bar) {
    int it = 0;
    while (!mbar_try(bar) && ++it < SPIN_LIMIT) {}
}
__device__ __forceinline__ void mbar_wait2(uint32_t bar0, uint32_t bar1) {
    int it = 0;
    while (!(mbar_try(bar0) & mbar_try(bar1)) && ++it < SPIN_LIMIT) {}
}
__device__ __forceinline__ void mbar_wait_cl(uint32_t bar) {
    uint32_t ok;
    int it = 0;
    do {
        asm volatile("{\n.reg .pred p;\nmbarrier.try_wait.parity.acquire.cluster.shared::cta.b64 p, [%1], 0;\nselp.u32 %0, 1, 0, p;\n}"
                     : "=r"(ok) : "r"(bar) : "memory");
    } while (!ok && ++it < SPIN_LIMIT);
}
__device__ __forceinline__ uint32_t mapa(uint32_t a, uint32_t rank) {
    uint32_t d;
    asm("mapa.shared::cluster.u32 %0, %1, %2;" : "=r"(d) : "r"(a), "r"(rank));
    return d;
}
__device__ __forceinline__ void st_async1(uint32_t dst, uint32_t v, uint32_t bar) {
    asm volatile("st.async.weak.shared::cluster.mbarrier::complete_tx::bytes.b32 [%0], %1, [%2];" ::"r"(dst), "r"(v), "r"(bar) : "memory");
}
__device__ __forceinline__ void st_async4(uint32_t dst, float a, float b, float c, float d, uint32_t bar) {
    asm volatile("st.async.weak.shared::cluster.mbarrier::complete_tx::bytes.v4.f32 [%0], {%1, %2, %3, %4}, [%5];"
                 ::"r"(dst), "f"(a), "f"(b), "f"(c), "f"(d), "r"(bar) : "memory");
}
__device__ __forceinline__ void bcast_word(const uint32_t (&rb)[CL], uint32_t off, uint32_t v, uint32_t bar_off) {
#pragma unroll
    for (int d = 0; d < CL; d++) st_async1(rb[d] + off, v, rb[d] + bar_off);
}
__device__ __forceinline__ void tma2d(uint32_t dst, const CUtensorMap* m, int c0, int c1, uint32_t bar) {
    asm volatile("cp.async.bulk.tensor.2d.shared::cluster.global.mbarrier::complete_tx::bytes [%0], [%1, {%3, %4}], [%2];"
                 ::"r"(dst), "l"(m), "r"(bar), "r"(c0), "r"(c1) : "memory");
}
__device__ __forceinline__ void tma3d(uint32_t dst, const CUtensorMap* m, int c0, int c1, int c2, uint32_t bar, uint64_t pol) {
    asm volatile("cp.async.bulk.tensor.3d.shared::cluster.global.mbarrier::complete_tx::bytes.L2::cache_hint [%0], [%1, {%3, %4, %5}], [%2], %6;"
                 ::"r"(dst), "l"(m), "r"(bar), "r"(c0), "r"(c1), "r"(c2), "l"(pol) : "memory");
}
__device__ __forceinline__ void ldsm4(uint32_t (&r)[4], uint32_t a) {
    asm volatile("ldmatrix.sync.aligned.m8n8.x4.shared.b16 {%0, %1, %2, %3}, [%4];"
                 : "=r"(r[0]), "=r"(r[1]), "=r"(r[2]), "=r"(r[3]) : "r"(a) : "memory");
}
__device__ __forceinline__ void ldsm4t(uint32_t (&r)[4], uint32_t a) {
    asm volatile("ldmatrix.sync.aligned.m8n8.x4.trans.shared.b16 {%0, %1, %2, %3}, [%4];"
                 : "=r"(r[0]), "=r"(r[1]), "=r"(r[2]), "=r"(r[3]) : "r"(a) : "memory");
}
__device__ __forceinline__ void mma16816(float (&c)[4], const uint32_t (&a)[4], uint32_t b0, uint32_t b1) {
    asm volatile("mma.sync.aligned.m16n8k16.row.col.f32.bf16.bf16.f32 {%0, %1, %2, %3}, {%4, %5, %6, %7}, {%8, %9}, {%0, %1, %2, %3};"
                 : "+f"(c[0]), "+f"(c[1]), "+f"(c[2]), "+f"(c[3])
                 : "r"(a[0]), "r"(a[1]), "r"(a[2]), "r"(a[3]), "r"(b0), "r"(b1));
}
__device__ __forceinline__ uint32_t lds32(uint32_t a) {
    uint32_t v;
    asm volatile("ld.shared.b32 %0, [%1];" : "=r"(v) : "r"(a) : "memory");
    return v;
}
__device__ __forceinline__ void cbar() { asm volatile("bar.sync 1, 256;" ::: "memory"); }

__device__ __forceinline__ void st_word(uint32_t* p, uint32_t v) {
    asm volatile("st.relaxed.gpu.global.b32 [%0], %1;" ::"l"(p), "r"(v) : "memory");
}
__device__ __forceinline__ uint4 ld_pkt(const uint32_t* p) {
    uint4 v;
    asm volatile("ld.relaxed.gpu.global.v4.b32 {%0, %1, %2, %3}, [%4];"
                 : "=r"(v.x), "=r"(v.y), "=r"(v.z), "=r"(v.w) : "l"(p) : "memory");
    return v;
}
__device__ __forceinline__ bool pkt_ok(const uint4& v, uint32_t tag) {
    return (((v.x ^ tag) | (v.y ^ tag) | (v.z ^ tag) | (v.w ^ tag)) & 3u) == 0u;
}
__device__ __forceinline__ void spin_cycles(uint32_t n) {
    uint32_t c0, c1;
    asm volatile("mov.u32 %0, %%clock;" : "=r"(c0));
    do { asm volatile("mov.u32 %0, %%clock;" : "=r"(c1)); } while (c1 - c0 < n);
}
__device__ __forceinline__ uint4 poll_pkt(const uint32_t* p, uint32_t tag) {
    uint4 v;
    int it = 0;
    do { v = ld_pkt(p); } while (!pkt_ok(v, tag) && ++it < SPIN_LIMIT);
    return v;
}
__device__ __forceinline__ void poll_pkt2(const uint32_t* p, const uint32_t* q, uint32_t tag, uint4& v, uint4& w) {
    int it = 0;
    do { v = ld_pkt(p); w = ld_pkt(q); } while (!(pkt_ok(v, tag) && pkt_ok(w, tag)) && ++it < SPIN_LIMIT);
}
__device__ __forceinline__ uint32_t pack2(float lo, float hi) {
    uint32_t u;
    asm("cvt.rn.bf16x2.f32 %0, %1, %2;" : "=r"(u) : "f"(hi), "f"(lo));
    return u;
}
__device__ __forceinline__ float rbf(float x) { return __uint_as_float(pack2(0.f, x)); }
__device__ __forceinline__ float ex2(float x) { float y; asm("ex2.approx.ftz.f32 %0, %1;" : "=f"(y) : "f"(x)); return y; }
__device__ __forceinline__ float rcp(float x) { float y; asm("rcp.approx.ftz.f32 %0, %1;" : "=f"(y) : "f"(x)); return y; }
__device__ __forceinline__ float sqrt_a(float x) { float y; asm("sqrt.approx.ftz.f32 %0, %1;" : "=f"(y) : "f"(x)); return y; }
constexpr float LOG2E = 1.4426950408889634f;
__device__ __forceinline__ uint32_t word_bf(float x_rounded, uint32_t tag) { return __float_as_uint(x_rounded) | tag; }
__device__ __forceinline__ uint32_t word_f32(float x, uint32_t tag) { return (__float_as_uint(x) & ~3u) | tag; }
__device__ __forceinline__ float unword(uint32_t w) { return __uint_as_float(w & ~3u); }
__device__ __forceinline__ float bf_lo(uint32_t w) { return __uint_as_float(w << 16); }
__device__ __forceinline__ float bf_hi(uint32_t w) { return __uint_as_float(w & 0xFFFF0000u); }
__device__ __forceinline__ uint32_t pack_hi(uint32_t a, uint32_t b) { return __byte_perm(a, b, 0x7632); }
__device__ __forceinline__ uint32_t gtime() { unsigned long long t; asm volatile("mov.u64 %0, %%globaltimer;" : "=l"(t)); return (uint32_t)t; }
__device__ __forceinline__ int mod_word(int c) { const int pb = c / 36; return MB_MOD + pb * 40 + (c - pb * 36); }

template <int LO, int HI>
__device__ __forceinline__ void init_bars(uint32_t bars) {
#pragma unroll
    for (int i = LO; i < HI; i++) mbar_init(bars + 8 * i, (i >= BAR_CV && i < BAR_DQ) ? 8 : 1);
}

#define STAMP(i)
#define PSTAMP(i)

__device__ __forceinline__ void ln_stats(const float* xs, int lane, float& mean_b, float& inv_den) {
    float v[18];
    const float c = xs[0];
#pragma unroll
    for (int i = 0; i < 4; i++) {
        const float4 a = *reinterpret_cast<const float4*>(xs + i * 128 + lane * 4);
        v[4 * i] = a.x; v[4 * i + 1] = a.y; v[4 * i + 2] = a.z; v[4 * i + 3] = a.w;
    }
    {
        const float2 a = *reinterpret_cast<const float2*>(xs + 512 + lane * 2);
        v[16] = a.x; v[17] = a.y;
    }
    float s0 = 0.f, s1 = 0.f, s2 = 0.f, q0 = 0.f, q1 = 0.f, q2 = 0.f;
#pragma unroll
    for (int i = 0; i < 18; i += 3) {
        const float d0 = v[i] - c, d1 = v[i + 1] - c, d2 = v[i + 2] - c;
        s0 += d0; s1 += d1; s2 += d2;
        q0 = fmaf(d0, d0, q0); q1 = fmaf(d1, d1, q1); q2 = fmaf(d2, d2, q2);
    }
    float s = (s0 + s1) + s2, q = (q0 + q1) + q2;
#pragma unroll
    for (int o = 16; o > 0; o >>= 1) {
        s += __shfl_xor_sync(0xffffffffu, s, o);
        q += __shfl_xor_sync(0xffffffffu, q, o);
    }
    const float md = s * (1.0f / 576.0f);
    const float var = fmaxf(fmaf(-md, md, q * (1.0f / 576.0f)), 0.f);
    mean_b = rbf(c + md);
    inv_den = rcp(rbf(sqrt_a(rbf(rbf(var) + 1e-5f))));
}

__device__ __forceinline__ void ld_ntile(uint32_t (&a)[6][4], uint32_t base_a, uint32_t base_b, int row0, int mi, int l7) {
    const int row = row0 + (mi >> 1) * 8 + l7;
    const uint32_t ra = base_a + row * 128, rb = base_b + row * 64;
#pragma unroll
    for (int m = 0; m < 4; m++) ldsm4t(a[m], ra + (((2 * m + (mi & 1)) ^ l7) << 4));
#pragma unroll
    for (int m = 0; m < 2; m++) ldsm4t(a[4 + m], rb + (((2 * m + (mi & 1)) ^ ((row >> 1) & 3)) << 4));
}

__global__ void __launch_bounds__(NTHREADS, 1)
adaln_attn_mlp_decode_kernel(const __grid_constant__ Maps maps, const Ptrs p) {
    extern __shared__ __align__(1024) uint8_t sm[];
    const uint32_t sb = smem_u32(sm);
    int tid, b, r;
    asm volatile("mov.u32 %0, %%tid.x;" : "=r"(tid));
    asm volatile("mov.u32 %0, %%ctaid.x;" : "=r"(b));
    asm volatile("mov.u32 %0, %%cluster_ctarank;" : "=r"(r));
    const int g = b / CL;
    const int nt = 21 + (r < 2);
    const uint32_t bars = sb + S_BARS;
    const int pos_m = b < NP1 ? 0 : 8, pos_q = b < NP1 ? 6 : 0;
    const int pos_o = P_KV + 2 * nt, pos_w1 = pos_o + 6, pos_w2 = pos_w1 + 9;

    if (tid >= 256) {
        if (tid == 256) {
            PSTAMP(16);
            if (sb & 1023u) __trap();
            init_bars<0, P_KV>(bars);
            asm volatile("fence.proxy.async.shared::cta;" ::: "memory");
        }
        __syncwarp();
        asm volatile("bar.arrive 2, 288;" ::: "memory");
        asm volatile("barrier.cluster.arrive.relaxed.aligned;" ::: "memory");
        uint64_t pol;
        asm volatile("createpolicy.fractional.L2::evict_first.b64 %0, 1.0;" : "=l"(pol));
        const float nsb_kv = (r < 2 ? BYTES_ALL / BYTES_22 : BYTES_ALL / BYTES_21) * __frcp_rn(T_RATE_KV);
        const float nsb_late = (r < 2 ? BYTES_ALL / BYTES_22 : BYTES_ALL / BYTES_21) * __frcp_rn(T_RATE_LATE);
        const uint32_t t0 = gtime();
        uint32_t tn = 0;
        uint32_t bar = bars;
        auto pace = [&](uint32_t t) { for (int it = 0; gtime() - t0 < t && it < SPIN_LIMIT; it++) {} };
#define ITEMLOG()
        if (tid == 256) {
            const uint32_t st_m = (uint32_t)(7680.f * nsb_kv), st_q = (uint32_t)(6144.f * nsb_kv);
#pragma unroll 1
            for (int ph = 0; ph < 2; ph++) {
                if ((ph == 0) == (b < NP1)) {
#pragma unroll 1
                    for (int i = 0; i < 6; i++) {
                        if (b >= NP1) { if (bar >= bars + 8 * T_WIN_KV) mbar_wait(bar - 8 * T_WIN_KV); pace(tn); }
                        ITEMLOG();
                        mbar_expect_tx(bar, 7680);
                        tma2d(sb + OFF_M + i * 7680, &maps.wmod, b * 36 - (b & 1) * 4, i * 96, bar);
                        bar += 8; tn += st_m;
                    }
                } else {
#pragma unroll 1
                    for (int i = 0; i < 8; i++) {
                        if (bar >= bars + 8 * T_WIN_KV) mbar_wait(bar - 8 * T_WIN_KV);
                        pace(b < NP1 ? (uint32_t)T_P1_Q_STEP * (i + 1) : tn);
                        ITEMLOG();
                        mbar_expect_tx(bar, 6144);
                        tma2d(sb + OFF_Q + i * 6144, &maps.wq, g * 256 + (i >> 1) * 64, r * 96 + (i & 1) * 48, bar);
                        bar += 8; tn += st_q;
                    }
                }
            }
        }
        asm volatile("bar.sync 3, 288;" ::: "memory");
        if (tid == 256) {
            const uint32_t st_kv = (uint32_t)(8192.f * nsb_kv), st_late8 = (uint32_t)(8192.f * nsb_late), st_late6 = (uint32_t)(6144.f * nsb_late);
            const int row0 = g * SK_ + (SK_ - WIN_) + (21 * r + (r < 2 ? r : 2)) * 32;
            uint32_t dst = sb + OFF_X + 12 * 8192;
            int row = row0;
#pragma unroll 1
            for (int i = 0; i < nt; i++) {
                if (i >= 14) mbar_wait2(bars + 8 * (BAR_CK + i - 14), bar - 8 * T_WIN_KV); else mbar_wait(bar - 8 * T_WIN_KV);
                pace(tn);
                ITEMLOG();
                mbar_expect_tx(bar, 8192);
                tma3d(dst, &maps.k, 0, row, 0, bar, pol);
                bar += 8; tn += st_kv; row += 32;
                dst += 8192; if (dst == sb + OFF_X + 14 * 8192) dst = sb + OFF_X;
            }
            PSTAMP(17);
            row = row0;
#pragma unroll 1
            for (int i = 0; i < nt; i++) {
                const bool late = i >= T_LATE_FROM;
                const uint32_t cons = bars + 8 * (i < 14 ? BAR_CK + nt + i - 14 : BAR_CV + i - 14);
                mbar_wait2(cons, bar - 8 * (late ? T_WIN_LATE : T_WIN_KV));
                pace(tn);
                ITEMLOG();
                mbar_expect_tx(bar, 8192);
                tma3d(dst, &maps.v, 0, row, 0, bar, pol);
                bar += 8; tn += late ? st_late8 : st_kv; row += 32;
                dst += 8192; if (dst == sb + OFF_X + 14 * 8192) dst = sb + OFF_X;
            }
            PSTAMP(18);
            const int ca = r * 96 + (r & 1) * 32, cb = r * 96 + ((r & 1) ? 0 : 64);
#pragma unroll
            for (int i = 0; i < 6; i++) {
                mbar_wait(bar - 8 * T_WIN_LATE);
                pace(tn);
                ITEMLOG();
                mbar_expect_tx(bar, 8192);
                if (i == 1 || i == 4) tma2d(sb + OFF_WOB + (i >> 2) * 8192, &maps.wob, cb, g * 256 + (i >> 2) * 128, bar);
                else { const int j = i == 0 ? 0 : (i == 5 ? 3 : i - 1); tma2d(sb + OFF_WOA + j * 8192, &maps.woa, ca, g * 256 + j * 64, bar); }
                bar += 8; tn += st_late8;
            }
            const uint32_t cv = bars + 8 * (BAR_CV + 30 - nt);
            const int c1a = g * 288 + (g & 1) * 32, c1b = g * 288 + ((g & 1) ? 0 : 256);
#pragma unroll
            for (int i = 0; i < 9; i++) {
                if (i == 7) mbar_wait2(cv, cv + 8);
                mbar_wait(bar - 8 * T_WIN_LATE);
                pace(tn);
                ITEMLOG();
                mbar_expect_tx(bar, 6144);
                if (i < 8) tma2d(sb + OFF_W1A + i * 6144, &maps.w1a, c1a + (i >> 1) * 64, r * 96 + (i & 1) * 48, bar);
                else tma2d(sb + OFF_W1B, &maps.w1b, c1b, r * 96, bar);
                bar += 8; tn += st_late6;
            }
            mbar_wait2(cv + 16, cv + 24);
            mbar_wait2(cv + 32, cv + 40);
            mbar_wait2(cv + 48, cv + 56);
#pragma unroll
            for (int i = 0; i < 9; i++) {
                mbar_wait(bar - 8 * T_WIN_LATE);
                pace(tn);
                ITEMLOG();
                mbar_expect_tx(bar, 6144);
                if (i % 3 == 1) tma2d(sb + OFF_W2B + (i / 3) * 6144, &maps.w2b, cb, g * 288 + (i / 3) * 96, bar);
                else { const int j = 2 * (i / 3) + (i % 3 == 2); tma2d(sb + OFF_W2A + j * 6144, &maps.w2a, ca, g * 288 + j * 48, bar); }
                bar += 8; tn += st_late6;
            }
            PSTAMP(19);
        }
        return;
    }

    const int lane = tid & 31, wid = tid >> 5;
    const int gq = lane >> 2, t4 = lane & 3;
    const int mi = lane >> 3, l7 = lane & 7;
    float* const xs = reinterpret_cast<float*>(sm + S_X);
    float* const part = reinterpret_cast<float*>(sm + S_PART);
    float* const red = reinterpret_cast<float*>(sm + S_RED);
    float* const inbox = reinterpret_cast<float*>(sm + S_IN);
    uint32_t* mail;
    asm volatile("mov.u64 %0, %1;" : "=l"(mail) : "l"(g_mail));
    STAMP(0);

    uint4 ldv = make_uint4(0u, 0u, 0u, 0u);
    if (tid < 72) ldv = *reinterpret_cast<const uint4*>(p.x + tid * 8);
    else if (tid >= 128 && tid < 200) ldv = *reinterpret_cast<const uint4*>(p.c + (tid - 128) * 8);
    else if (tid == 255) asm volatile("ld.relaxed.gpu.global.b32 %0, [%1];" : "=r"(ldv.x) : "l"(&g_count) : "memory");
    if (lane == 0) {
        constexpr int NB = N_BARS - P_KV, Q = (NB + 7) / 8;
        switch (wid) {
            case 0: init_bars<P_KV + 0 * Q, P_KV + 1 * Q>(bars); break;
            case 1: init_bars<P_KV + 1 * Q, P_KV + 2 * Q>(bars); break;
            case 2: init_bars<P_KV + 2 * Q, P_KV + 3 * Q>(bars); break;
            case 3: init_bars<P_KV + 3 * Q, P_KV + 4 * Q>(bars); break;
            case 4: init_bars<P_KV + 4 * Q, P_KV + 5 * Q>(bars); break;
            case 5: init_bars<P_KV + 5 * Q, P_KV + 6 * Q>(bars); break;
            case 6: init_bars<P_KV + 6 * Q, P_KV + 7 * Q>(bars); break;
            default:
                init_bars<P_KV + 7 * Q, N_BARS>(bars);
                static_assert(P_KV + 7 * Q <= BAR_DQ, "the last warp arms the exchange barriers");
                mbar_expect_tx(bars + 8 * BAR_DQ, CL * 1024);
                mbar_expect_tx(bars + 8 * BAR_DS, CL * 16);
                mbar_expect_tx(bars + 8 * BAR_DO, CL * 1024);
                mbar_expect_tx(bars + 8 * BAR_DX, CL * 384);
                mbar_expect_tx(bars + 8 * BAR_DH, CL * 1152);
                break;
        }
        asm volatile("fence.mbarrier_init.release.cluster;" ::: "memory");
        asm volatile("fence.proxy.async.shared::cta;" ::: "memory");
    }
    __syncwarp();
    asm volatile("bar.arrive 3, 288;" ::: "memory");
    asm volatile("barrier.cluster.arrive.relaxed.aligned;" ::: "memory");
    if (tid < 96) { st_word(mail + MB_P1 + b * 96 + tid, 0u); st_word(mail + MB_P2 + b * 96 + tid, 0u); }
    if (tid >= 96 && tid < 136) st_word(mail + MB_MOD + b * 40 + tid - 96, 0u);
    if (tid < 72) {
        *reinterpret_cast<float4*>(xs + tid * 8) = make_float4(bf_lo(ldv.x), bf_hi(ldv.x), bf_lo(ldv.y), bf_hi(ldv.y));
        *reinterpret_cast<float4*>(xs + tid * 8 + 4) = make_float4(bf_lo(ldv.z), bf_hi(ldv.z), bf_lo(ldv.w), bf_hi(ldv.w));
    } else if (tid >= 128 && tid < 200) {
        const uint32_t w[4] = {ldv.x, ldv.y, ldv.z, ldv.w};
        uint32_t o[4];
#pragma unroll
        for (int j = 0; j < 4; j++) {
            const float lo = bf_lo(w[j]), hi = bf_hi(w[j]);
            o[j] = pack2(lo * rcp(1.0f + ex2(-lo * LOG2E)), hi * rcp(1.0f + ex2(-hi * LOG2E)));
        }
        *reinterpret_cast<uint4*>(sm + S_P + (tid - 128) * 16) = make_uint4(o[0], o[1], o[2], o[3]);
    } else if (tid == 255) {
        reinterpret_cast<uint32_t*>(sm + S_MISC)[0] = ldv.x;
    }
    asm volatile("bar.sync 2, 288;" ::: "memory");
    const uint32_t cnt = reinterpret_cast<const uint32_t*>(sm + S_MISC)[0];
    const uint32_t tag = 1u + cnt;

    const int pc = (wid < 6 ? wid : 0) * 4 + t4;
    const float4 xown = *reinterpret_cast<const float4*>(xs + r * 96 + pc * 4);
    float xn[4] = {0.f, 0.f, 0.f, 0.f};
    if (wid == 0) {
        float mean_b, inv_den;
        ln_stats(xs, lane, mean_b, inv_den);
        const float4 v = *reinterpret_cast<const float4*>(xs + r * 96 + (lane < 24 ? lane : 0) * 4);
        xn[0] = rbf(rbf(v.x - mean_b) * inv_den); xn[1] = rbf(rbf(v.y - mean_b) * inv_den);
        xn[2] = rbf(rbf(v.z - mean_b) * inv_den); xn[3] = rbf(rbf(v.w - mean_b) * inv_den);
    }
    asm volatile("barrier.cluster.wait.acquire.aligned;" ::: "memory");

    uint32_t rb[CL];
#pragma unroll
    for (int d = 0; d < CL; d++) rb[d] = mapa(sb, d);
    const int ca_off = (r & 1) * 32, cb_off = (r & 1) ? 0 : 64;
    float acc[6][4];
#pragma unroll 1
    for (int ph = 0; ph < 2; ph++) {
        if ((ph == 0) == (b < NP1)) {
#pragma unroll
            for (int m = 0; m < 3; m++) { acc[m][0] = acc[m][1] = acc[m][2] = acc[m][3] = 0.f; }
            const uint32_t base = sb + OFF_M + (wid * 16 + (mi >> 1) * 8 + l7) * 80 + (mi & 1) * 16;
#pragma unroll
            for (int i = 0; i < 5; i++) {
                const int s = wid + 8 * i;
                if (i < 4 || wid < 4) {
                    const uint32_t b0 = lds32(sb + S_P + (s * 16 + 2 * t4) * 2), b1 = lds32(sb + S_P + (s * 16 + 8 + 2 * t4) * 2);
                    mbar_wait(bars + 8 * (pos_m + s / 6));
#pragma unroll
                    for (int m = 0; m < 3; m++) {
                        uint32_t a[4];
                        ldsm4t(a, base + i * (128 * 80) + m * 32);
                        mma16816(acc[m], a, b0, b1);
                    }
                }
            }
            if (t4 == 0) {
#pragma unroll
                for (int m = 0; m < 3; m++) { part[wid * 48 + m * 16 + gq] = acc[m][0]; part[wid * 48 + m * 16 + 8 + gq] = acc[m][2]; }
            }
            cbar();
            if (tid < 40) {
                const float* pp = part + tid;
                float m = rbf(((pp[0] + pp[48]) + (pp[96] + pp[144])) + ((pp[192] + pp[240]) + (pp[288] + pp[336])));
                const int u = tid - (b & 1) * 4;
                const int col = b * 36 + u;
                if ((col >= 576 && col < 1152) || (col >= 2304 && col < 2880)) m = rbf(1.0f + m);
                st_word(mail + MB_MOD + b * 40 + (u >= 0 && u < 36 ? u : (u < 0 ? u + 40 : u)), word_bf(m, tag));
            }
            STAMP(1);
            cbar();
        }
        if (ph == 1) break;

        if (tid < 24) {
            uint4 sa, ca;
            poll_pkt2(mail + mod_word(r * 96 + tid * 4), mail + mod_word(576 + r * 96 + tid * 4), tag, sa, ca);
            const float h0 = rbf(xn[0] * bf_hi(ca.x)) + bf_hi(sa.x), h1 = rbf(xn[1] * bf_hi(ca.y)) + bf_hi(sa.y);
            const float h2 = rbf(xn[2] * bf_hi(ca.z)) + bf_hi(sa.z), h3 = rbf(xn[3] * bf_hi(ca.w)) + bf_hi(sa.w);
            *reinterpret_cast<uint2*>(sm + S_H + tid * 8) = make_uint2(pack2(h0, h1), pack2(h2, h3));
        }
        cbar();
        STAMP(2);

        const int cb = wid >> 1;
        mbar_wait2(bars + 8 * (pos_q + 2 * cb), bars + 8 * (pos_q + 2 * cb + 1));
        float c0[4] = {0.f, 0.f, 0.f, 0.f}, c1[4] = {0.f, 0.f, 0.f, 0.f};
#pragma unroll
        for (int s = 0; s < 6; s++) {
            const int row = s * 16 + (mi >> 1) * 8 + l7;
            const uint32_t ra = sb + OFF_Q + cb * 12288 + row * 128;
            const int ch = (wid & 1) * 4 + (mi & 1);
            uint32_t a0[4], a1[4];
            ldsm4t(a0, ra + ((ch ^ l7) << 4));
            ldsm4t(a1, ra + (((ch + 2) ^ l7) << 4));
            const uint32_t b0 = lds32(sb + S_H + (s * 16 + 2 * t4) * 2), b1 = lds32(sb + S_H + (s * 16 + 8 + 2 * t4) * 2);
            mma16816(c0, a0, b0, b1);
            mma16816(c1, a1, b0, b1);
        }
        const float v = (t4 & 2) ? ((t4 & 1) ? c1[2] : c1[0]) : ((t4 & 1) ? c0[2] : c0[0]);
        bcast_word(rb, S_IN + (r * 288 + wid * 32 + (t4 >> 1) * 16 + (t4 & 1) * 8 + gq) * 4, __float_as_uint(v), S_BARS + 8 * BAR_DQ);
        STAMP(3);
    }
    mbar_wait_cl(bars + 8 * BAR_DQ);
    {
        const float* in = inbox + tid;
        const float q = ((in[0] + in[288]) + (in[576] + in[864])) + (in[1152] + in[1440]);
        reinterpret_cast<uint16_t*>(sm + S_QS)[tid] = (uint16_t)pack2(q, 0.f);
    }
    cbar();
    STAMP(4);

    float sv[2][4];
    {
        uint32_t qb[8][2];
#pragma unroll
        for (int s = 0; s < 8; s++) {
            qb[s][0] = lds32(sb + S_QS + ((gq & 1) * 128 + s * 16 + 2 * t4) * 2);
            qb[s][1] = lds32(sb + S_QS + ((gq & 1) * 128 + s * 16 + 8 + 2 * t4) * 2);
        }
#pragma unroll
        for (int e = 0; e < 4; e++) sv[0][e] = sv[1][e] = -INFINITY;
#pragma unroll
        for (int i = 0; i < 3; i++) {
            const int j = wid + 8 * i;
            if (j < nt) {
                const int slot = j < 2 ? j + 12 : (j < 16 ? j - 2 : j - 16);
                const uint32_t base = sb + OFF_X + slot * 8192;
                mbar_wait(bars + 8 * (P_KV + j));
                float c[2][4] = {{0.f, 0.f, 0.f, 0.f}, {0.f, 0.f, 0.f, 0.f}};
#pragma unroll
                for (int s = 0; s < 8; s++) {
#pragma unroll
                    for (int m = 0; m < 2; m++) {
                        const int row = m * 16 + (mi & 1) * 8 + l7;
                        const int ch = 2 * (s & 3) + (mi >> 1);
                        uint32_t a[4];
                        ldsm4(a, base + (s >> 2) * 4096 + row * 128 + ((ch ^ l7) << 4));
                        mma16816(c[m], a, qb[s][0], qb[s][1]);
                    }
                }
                __syncwarp();
                if (lane == 0) mbar_arrive(bars + 8 * (BAR_CK + j));
#pragma unroll
                for (int m = 0; m < 2; m++) {
                    if (t4 == ((i * 2 + m) & 3)) {
#pragma unroll
                        for (int e = 0; e < 4; e++) sv[i >> 1][e] = rbf(rbf(c[m][e]) * 0.08838834764831845f);
                    }
                }
            }
        }
    }
    STAMP(5);

    {
        float m0 = fmaxf(fmaxf(sv[0][0], sv[0][2]), fmaxf(sv[1][0], sv[1][2]));
        float m1 = fmaxf(fmaxf(sv[0][1], sv[0][3]), fmaxf(sv[1][1], sv[1][3]));
#pragma unroll
        for (int o = 16; o > 0; o >>= 1) {
            m0 = fmaxf(m0, __shfl_xor_sync(0xffffffffu, m0, o));
            m1 = fmaxf(m1, __shfl_xor_sync(0xffffffffu, m1, o));
        }
        if (lane == 0) { red[wid * 2] = m0; red[wid * 2 + 1] = m1; }
        cbar();
#pragma unroll
        for (int w = 0; w < 8; w++) { m0 = fmaxf(m0, red[w * 2]); m1 = fmaxf(m1, red[w * 2 + 1]); }
        uint16_t* P = reinterpret_cast<uint16_t*>(sm + S_P);
        float l0 = 0.f, l1 = 0.f;
#pragma unroll
        for (int h = 0; h < 2; h++) {
            const int j = wid + 8 * (2 * h + (t4 >> 1));
            if ((h == 0 || t4 < 2) && j < nt) {
                const float e0 = ex2((sv[h][0] - m0) * LOG2E), e1 = ex2((sv[h][1] - m1) * LOG2E);
                const float e2 = ex2((sv[h][2] - m0) * LOG2E), e3 = ex2((sv[h][3] - m1) * LOG2E);
                const int key = j * 32 + (t4 & 1) * 16 + gq;
                const uint32_t p01 = pack2(e0, e1), p23 = pack2(e2, e3);
                P[key] = (uint16_t)p01; P[key + 8] = (uint16_t)p23;
                P[PROW + key] = (uint16_t)(p01 >> 16); P[PROW + key + 8] = (uint16_t)(p23 >> 16);
                l0 += e0 + e2; l1 += e1 + e3;
            }
        }
#pragma unroll
        for (int o = 16; o > 0; o >>= 1) {
            l0 += __shfl_xor_sync(0xffffffffu, l0, o);
            l1 += __shfl_xor_sync(0xffffffffu, l1, o);
        }
        if (lane == 0) { red[16 + wid * 2] = l0; red[16 + wid * 2 + 1] = l1; }
        cbar();
        if (tid < 24) {
            const int dst = tid >> 2, e = tid & 3;
            float l = 0.f;
#pragma unroll
            for (int w = 0; w < 8; w++) l += red[16 + w * 2 + (e >> 1)];
            const float v = (e & 1) ? l : ((e >> 1) ? m1 : m0);
            st_async1(mapa(sb + S_ST + (r * 4 + e) * 4, dst), __float_as_uint(v), mapa(bars + 8 * BAR_DS, dst));
        }
    }
    STAMP(6);

    const uint32_t* modp;
    {
        const int t = tid < 96 ? tid : 0, v = t / 24, j = t - v * 24;
        modp = mail + mod_word((v == 0 ? 1152 : (v == 1 ? 2880 : (v == 2 ? 1728 : 2304))) + r * 96 + j * 4);
    }
    uint4 modw = make_uint4(0u, 0u, 0u, 0u);
    if (tid < 96) modw = ld_pkt(modp);

    {
        float c0[4] = {0.f, 0.f, 0.f, 0.f}, c1[4] = {0.f, 0.f, 0.f, 0.f};
        const uint32_t pb = sb + S_P + (gq & 1) * (PROW * 2) + t4 * 4;
        const int ch = 2 * (wid & 3) + (mi & 1);
        const uint32_t aoff = (wid >> 2) * 4096 + ((mi >> 1) * 8 + l7) * 128 + ((ch ^ l7) << 4);
        int slot = nt + 12 - 28;
#pragma unroll 1
        for (int j = 0; j < nt; j++) {
            const uint32_t base = sb + OFF_X + slot * 8192 + aoff;
            const uint32_t b0 = lds32(pb + j * 64), b1 = lds32(pb + j * 64 + 16);
            const uint32_t b2 = lds32(pb + j * 64 + 32), b3 = lds32(pb + j * 64 + 48);
            mbar_wait(bars + 8 * (P_KV + nt + j));
            uint32_t a0[4], a1[4];
            ldsm4t(a0, base);
            ldsm4t(a1, base + 2048);
            mma16816(c0, a0, b0, b1);
            mma16816(c1, a1, b2, b3);
            __syncwarp();
            if (lane == 0) mbar_arrive(bars + 8 * (BAR_CV + j));
            if (++slot == 14) slot = 0;
            if (j == 12 && wid == 0) {
                mbar_wait_cl(bars + 8 * BAR_DS);
                const int src = lane & 7, hh = (lane >> 3) & 1;
                const float2 st = *reinterpret_cast<const float2*>(sm + S_ST + ((src < CL ? src : 0) * 4 + hh * 2) * 4);
                const float m = src < CL ? st.x : -INFINITY;
                float M = m;
#pragma unroll
                for (int o = 1; o < 8; o <<= 1) M = fmaxf(M, __shfl_xor_sync(0xffffffffu, M, o));
                const float w = src < CL ? ex2((m - M) * LOG2E) : 0.f;
                float L = w * (src < CL ? st.y : 0.f);
#pragma unroll
                for (int o = 1; o < 8; o <<= 1) L += __shfl_xor_sync(0xffffffffu, L, o);
                if (lane < 16) reinterpret_cast<float*>(sm + S_F)[lane] = __fdiv_rn(w, L);
            }
            if (j == 9 && tid < 96) {
                if (!pkt_ok(modw, tag)) modw = poll_pkt(modp, tag);
                *reinterpret_cast<float4*>(sm + S_G + tid * 16) = make_float4(bf_hi(modw.x), bf_hi(modw.y), bf_hi(modw.z), bf_hi(modw.w));
            }
            if (j == 13 && wid != 0) mbar_wait_cl(bars + 8 * BAR_DS);
        }
        const float v = (t4 & 2) ? ((t4 & 1) ? c0[3] + c1[3] : c0[2] + c1[2]) : ((t4 & 1) ? c0[1] + c1[1] : c0[0] + c1[0]);
        bcast_word(rb, S_IN + (r * 288 + (t4 & 1) * 128 + wid * 16 + gq + (t4 >> 1) * 8) * 4, __float_as_uint(v), S_BARS + 8 * BAR_DO);
    }
    STAMP(7);
    cbar();
    {
        const float* f = reinterpret_cast<const float*>(sm + S_F) + (tid >> 7) * 8;
        const float f0 = f[0], f1 = f[1], f2 = f[2], f3 = f[3], f4 = f[4], f5 = f[5];
        mbar_wait_cl(bars + 8 * BAR_DO);
        const float* in = inbox + tid;
        const float o = (fmaf(f0, in[0], f1 * in[288]) + fmaf(f2, in[576], f3 * in[864])) + fmaf(f4, in[1152], f5 * in[1440]);
        reinterpret_cast<uint16_t*>(sm + S_QS)[tid] = (uint16_t)pack2(o, 0.f);
    }
    cbar();
    STAMP(8);

    {
#pragma unroll
        for (int m = 0; m < 6; m++) { acc[m][0] = acc[m][1] = acc[m][2] = acc[m][3] = 0.f; }
        uint32_t ob[2][2];
#pragma unroll
        for (int i = 0; i < 2; i++) {
            ob[i][0] = lds32(sb + S_QS + ((2 * wid + i) * 16 + 2 * t4) * 2);
            ob[i][1] = lds32(sb + S_QS + ((2 * wid + i) * 16 + 8 + 2 * t4) * 2);
        }
        mbar_wait2(bars + 8 * (pos_o + pos_a(wid >> 1)), bars + 8 * (pos_o + pos_b(wid >> 2)));
#pragma unroll
        for (int i = 0; i < 2; i++) {
            uint32_t a[6][4];
            ld_ntile(a, sb + OFF_WOA, sb + OFF_WOB, (2 * wid + i) * 16, mi, l7);
#pragma unroll
            for (int m = 0; m < 6; m++) mma16816(acc[m], a[m], ob[i][0], ob[i][1]);
        }
        if (t4 == 0) {
#pragma unroll
            for (int m = 0; m < 6; m++) {
                const int cm = m < 4 ? m * 16 + ca_off : (m - 4) * 16 + cb_off;
                part[wid * 96 + cm + gq] = acc[m][0]; part[wid * 96 + cm + 8 + gq] = acc[m][2];
            }
        }
        cbar();
        if (tid < 96) {
            const float* pp = part + tid;
            const float s = ((pp[0] + pp[96]) + (pp[192] + pp[288])) + ((pp[384] + pp[480]) + (pp[576] + pp[672]));
            st_word(mail + MB_P1 + b * 96 + tid, word_f32(s, tag));
        }
    }
    STAMP(9);

    if (wid < 6) {
        const float4 ga = *reinterpret_cast<const float4*>(sm + S_G + pc * 16);
        const uint32_t* src = mail + MB_P1 + ((lane >> 2) * CL + r) * 96 + pc * 4;
        if (T_DELAY_G1 > 0) spin_cycles(T_DELAY_G1);
        uint4 u, w;
        poll_pkt2(src, src + 8 * CL * 96, tag, u, w);
        float a0 = unword(u.x) + unword(w.x), a1 = unword(u.y) + unword(w.y);
        float a2 = unword(u.z) + unword(w.z), a3 = unword(u.w) + unword(w.w);
#pragma unroll
        for (int o = 4; o < 32; o <<= 1) {
            a0 += __shfl_xor_sync(0xffffffffu, a0, o);
            a1 += __shfl_xor_sync(0xffffffffu, a1, o);
            a2 += __shfl_xor_sync(0xffffffffu, a2, o);
            a3 += __shfl_xor_sync(0xffffffffu, a3, o);
        }
        a0 = rbf(xown.x + rbf(ga.x * rbf(a0))); a1 = rbf(xown.y + rbf(ga.y * rbf(a1)));
        a2 = rbf(xown.z + rbf(ga.z * rbf(a2))); a3 = rbf(xown.w + rbf(ga.w * rbf(a3)));
        if (gq < CL) st_async4(mapa(sb + S_X + (r * 96 + pc * 4) * 4, gq), a0, a1, a2, a3, mapa(bars + 8 * BAR_DX, gq));
    }
    STAMP(10);

    uint32_t w1f[3][6][4];
    {
        const uint32_t wb = bars + 8 * pos_w1;
        mbar_wait2(wb + 16 * (wid >> 2), wb + 16 * (wid >> 2) + 8);
        mbar_wait2(wb + 16 * (2 + (wid >> 2)), wb + 16 * (2 + (wid >> 2)) + 8);
        if (wid < 2) mbar_wait(wb + 64);
#pragma unroll
        for (int s = 0; s < 6; s++) {
            const int row = s * 16 + (mi >> 1) * 8 + l7;
            const uint32_t ra = sb + OFF_W1A + (wid >> 2) * 12288 + row * 128 + (((2 * (wid & 3) + (mi & 1)) ^ l7) << 4);
            ldsm4t(w1f[0][s], ra);
            ldsm4t(w1f[1][s], ra + 2 * 12288);
            if (wid < 2) ldsm4t(w1f[2][s], sb + OFF_W1B + row * 64 + (((2 * wid + (mi & 1)) ^ ((row >> 1) & 3)) << 4));
            else { w1f[2][s][0] = w1f[2][s][1] = w1f[2][s][2] = w1f[2][s][3] = 0u; }
        }
    }

    if (wid == 0) {
        const int j = lane < 24 ? lane : 0;
        const float4 sv2 = *reinterpret_cast<const float4*>(sm + S_G + 768 + j * 16);
        const float4 cb = *reinterpret_cast<const float4*>(sm + S_G + 1152 + j * 16);
        mbar_wait_cl(bars + 8 * BAR_DX);
        STAMP(11);
        const float4 v = *reinterpret_cast<const float4*>(xs + r * 96 + j * 4);
        float mean_b, inv_den;
        ln_stats(xs, lane, mean_b, inv_den);
        const float h0 = rbf(rbf(rbf(v.x - mean_b) * inv_den) * cb.x) + sv2.x;
        const float h1 = rbf(rbf(rbf(v.y - mean_b) * inv_den) * cb.y) + sv2.y;
        const float h2 = rbf(rbf(rbf(v.z - mean_b) * inv_den) * cb.z) + sv2.z;
        const float h3 = rbf(rbf(rbf(v.w - mean_b) * inv_den) * cb.w) + sv2.w;
        if (lane < 24) *reinterpret_cast<uint2*>(sm + S_H + lane * 8) = make_uint2(pack2(h0, h1), pack2(h2, h3));
    }
    cbar();
    STAMP(12);

    {
        uint32_t hb[6][2];
#pragma unroll
        for (int s = 0; s < 6; s++) { hb[s][0] = lds32(sb + S_H + (s * 16 + 2 * t4) * 2); hb[s][1] = lds32(sb + S_H + (s * 16 + 8 + 2 * t4) * 2); }
#pragma unroll
        for (int m = 0; m < 6; m++) { acc[m][0] = acc[m][1] = acc[m][2] = acc[m][3] = 0.f; }
#pragma unroll
        for (int s = 0; s < 6; s++) {
            mma16816(acc[(s & 1) * 3 + 0], w1f[0][s], hb[s][0], hb[s][1]);
            mma16816(acc[(s & 1) * 3 + 1], w1f[1][s], hb[s][0], hb[s][1]);
            if (wid < 2) mma16816(acc[(s & 1) * 3 + 2], w1f[2][s], hb[s][0], hb[s][1]);
        }
        const int ua = (g & 1) * 32, ub = (g & 1) ? 0 : 256;
        const float v = (t4 & 2) ? ((t4 & 1) ? acc[1][2] + acc[4][2] : acc[1][0] + acc[4][0]) : ((t4 & 1) ? acc[0][2] + acc[3][2] : acc[0][0] + acc[3][0]);
        bcast_word(rb, S_IN + (r * 288 + ua + (wid + (t4 >> 1) * 8) * 16 + (t4 & 1) * 8 + gq) * 4, __float_as_uint(v), S_BARS + 8 * BAR_DH);
        if (wid < 2 && t4 < 2)
            bcast_word(rb, S_IN + (r * 288 + ub + wid * 16 + t4 * 8 + gq) * 4,
                       __float_as_uint(t4 ? acc[2][2] + acc[5][2] : acc[2][0] + acc[5][0]), S_BARS + 8 * BAR_DH);
    }
    STAMP(13);

    {
        uint32_t w2f[3][6][4];
        const uint32_t wb = bars + 8 * pos_w2;
        const uint32_t ba0 = wb + 8 * pos_a(wid / 3), bb0 = wb + 8 * pos_b(wid / 6);
        const uint32_t ba1 = wb + 8 * pos_a((wid + 8) / 3), bb1 = wb + 8 * pos_b((wid + 8) / 6);
        const uint32_t ba2 = wb + 8 * pos_a(5), bb2 = wb + 8 * pos_b(2);
        const bool pre = mbar_test(ba0) & mbar_test(bb0) & mbar_test(ba1) & mbar_test(bb1) & mbar_test(ba2) & mbar_test(bb2);
        if (pre) {
            ld_ntile(w2f[0], sb + OFF_W2A, sb + OFF_W2B, wid * 16, mi, l7);
            ld_ntile(w2f[1], sb + OFF_W2A, sb + OFF_W2B, (wid + 8) * 16, mi, l7);
            if (wid < 2) ld_ntile(w2f[2], sb + OFF_W2A, sb + OFF_W2B, (wid + 16) * 16, mi, l7);
        }
        mbar_wait_cl(bars + 8 * BAR_DH);
#pragma unroll
        for (int i = 0; i < 2; i++) {
            if (i == 0 || tid < 32) {
                const float* in = inbox + tid + i * 256;
                const float tv = rbf(((in[0] + in[288]) + (in[576] + in[864])) + (in[1152] + in[1440]));
                reinterpret_cast<uint16_t*>(sm + S_HV)[tid + i * 256] = (uint16_t)pack2(tv * rcp(1.0f + ex2(-tv * LOG2E)), 0.f);
            }
        }
        cbar();
        STAMP(21);
        uint32_t vb[3][2];
#pragma unroll
        for (int i = 0; i < 3; i++) {
            const int s = wid + 8 * ((i < 2 || wid < 2) ? i : 0);
            vb[i][0] = lds32(sb + S_HV + (s * 16 + 2 * t4) * 2);
            vb[i][1] = lds32(sb + S_HV + (s * 16 + 8 + 2 * t4) * 2);
        }
#pragma unroll
        for (int m = 0; m < 6; m++) { acc[m][0] = acc[m][1] = acc[m][2] = acc[m][3] = 0.f; }
#pragma unroll
        for (int i = 0; i < 3; i++) {
            if (i < 2 || wid < 2) {
                if (!pre) {
                    if (i == 0) mbar_wait2(ba0, bb0); else if (i == 1) mbar_wait2(ba1, bb1); else mbar_wait2(ba2, bb2);
                    ld_ntile(w2f[i], sb + OFF_W2A, sb + OFF_W2B, (wid + 8 * i) * 16, mi, l7);
                }
#pragma unroll
                for (int m = 0; m < 6; m++) mma16816(acc[m], w2f[i][m], vb[i][0], vb[i][1]);
            }
        }
        if (t4 == 0) {
#pragma unroll
            for (int m = 0; m < 6; m++) {
                const int cm = m < 4 ? m * 16 + ca_off : (m - 4) * 16 + cb_off;
                part[wid * 96 + cm + gq] = acc[m][0]; part[wid * 96 + cm + 8 + gq] = acc[m][2];
            }
        }
        cbar();
        if (tid < 96) {
            const float* pp = part + tid;
            const float s = ((pp[0] + pp[96]) + (pp[192] + pp[288])) + ((pp[384] + pp[480]) + (pp[576] + pp[672]));
            st_word(mail + MB_P2 + b * 96 + tid, word_f32(s, tag));
        }
    }
    STAMP(14);

    if (g < 12 && wid == 0) {
        const int col = g * 8 + (lane & 1) * 4;
        const float4 gb = *reinterpret_cast<const float4*>(sm + S_G + 384 + col * 4);
        const float4 x2 = *reinterpret_cast<const float4*>(xs + r * 96 + col);
        if (T_DELAY_G2 > 0) spin_cycles(T_DELAY_G2);
        const uint4 u = poll_pkt(mail + MB_P2 + ((lane >> 1) * CL + r) * 96 + col, tag);
        float a0 = unword(u.x), a1 = unword(u.y), a2 = unword(u.z), a3 = unword(u.w);
#pragma unroll
        for (int o = 2; o < 32; o <<= 1) {
            a0 += __shfl_xor_sync(0xffffffffu, a0, o);
            a1 += __shfl_xor_sync(0xffffffffu, a1, o);
            a2 += __shfl_xor_sync(0xffffffffu, a2, o);
            a3 += __shfl_xor_sync(0xffffffffu, a3, o);
        }
        if (lane < 2) {
            const uint2 o = make_uint2(pack2(x2.x + rbf(gb.x * rbf(a0)), x2.y + rbf(gb.y * rbf(a1))),
                                       pack2(x2.z + rbf(gb.z * rbf(a2)), x2.w + rbf(gb.w * rbf(a3))));
            *reinterpret_cast<uint2*>(p.out + r * 96 + col) = o;
        }
        if (b == 0 && lane == 0) g_count = (cnt >= 2u) ? 0u : cnt + 1u;
    }
    STAMP(15);
}

typedef CUresult (*EncodeTiledFn)(CUtensorMap*, CUtensorMapDataType, cuuint32_t, void*, const cuuint64_t*, const cuuint64_t*,
                                  const cuuint32_t*, const cuuint32_t*, CUtensorMapInterleave, CUtensorMapSwizzle,
                                  CUtensorMapL2promotion, CUtensorMapFloatOOBfill);

void encode2d(EncodeTiledFn enc, CUtensorMap* m, const void* ptr, uint64_t cols, uint64_t rows, uint32_t bc, uint32_t br,
              CUtensorMapSwizzle sw) {
    cuuint64_t dims[2] = {cols, rows};
    cuuint64_t str[1] = {cols * 2};
    cuuint32_t box[2] = {bc, br};
    cuuint32_t es[2] = {1, 1};
    enc(m, CU_TENSOR_MAP_DATA_TYPE_BFLOAT16, 2, const_cast<void*>(ptr), dims, str, box, es, CU_TENSOR_MAP_INTERLEAVE_NONE, sw,
        CU_TENSOR_MAP_L2_PROMOTION_L2_128B, CU_TENSOR_MAP_FLOAT_OOB_FILL_NONE);
}
void encode_kv(EncodeTiledFn enc, CUtensorMap* m, const void* ptr) {
    cuuint64_t dims[3] = {64, 16ull * SK_, 2};
    cuuint64_t str[2] = {256, 128};
    cuuint32_t box[3] = {64, 32, 2};
    cuuint32_t es[3] = {1, 1, 1};
    enc(m, CU_TENSOR_MAP_DATA_TYPE_BFLOAT16, 3, const_cast<void*>(ptr), dims, str, box, es, CU_TENSOR_MAP_INTERLEAVE_NONE,
        CU_TENSOR_MAP_SWIZZLE_128B, CU_TENSOR_MAP_L2_PROMOTION_L2_128B, CU_TENSOR_MAP_FLOAT_OOB_FILL_NONE);
}

}

extern "C" void kernel_launch(void* const* d_in, const int* in_sizes, int n_in, void* d_out, int out_size) {
    (void)in_sizes; (void)n_in; (void)out_size;
    static EncodeTiledFn enc = nullptr;
    if (!enc) {
        void* fn = nullptr;
        cudaDriverEntryPointQueryResult qr;
        cudaGetDriverEntryPoint("cuTensorMapEncodeTiled", &fn, cudaEnableDefault, &qr);
        enc = (EncodeTiledFn)fn;
        cudaFuncSetAttribute(adaln_attn_mlp_decode_kernel, cudaFuncAttributeMaxDynamicSharedMemorySize, SMEM_BYTES);
    }
    Maps maps;
    encode2d(enc, &maps.wmod, d_in[9], 3456, 576, 40, 96, CU_TENSOR_MAP_SWIZZLE_NONE);
    encode2d(enc, &maps.wq, d_in[3], 4096, 576, 64, 48, CU_TENSOR_MAP_SWIZZLE_128B);
    encode_kv(enc, &maps.k, d_in[1]);
    encode_kv(enc, &maps.v, d_in[2]);
    encode2d(enc, &maps.woa, d_in[4], 576, 4096, 64, 64, CU_TENSOR_MAP_SWIZZLE_128B);
    encode2d(enc, &maps.wob, d_in[4], 576, 4096, 32, 128, CU_TENSOR_MAP_SWIZZLE_64B);
    encode2d(enc, &maps.w1a, d_in[6], F_, 576, 64, 48, CU_TENSOR_MAP_SWIZZLE_128B);
    encode2d(enc, &maps.w1b, d_in[6], F_, 576, 32, 96, CU_TENSOR_MAP_SWIZZLE_64B);
    encode2d(enc, &maps.w2a, d_in[7], 576, F_, 64, 48, CU_TENSOR_MAP_SWIZZLE_128B);
    encode2d(enc, &maps.w2b, d_in[7], 576, F_, 32, 96, CU_TENSOR_MAP_SWIZZLE_64B);
    Ptrs p;
    p.x = (const __nv_bfloat16*)d_in[0];
    p.c = (const __nv_bfloat16*)d_in[8];
    p.out = (__nv_bfloat16*)d_out;
    cudaLaunchConfig_t cfg = {};
    cfg.gridDim = dim3(NCTA);
    cfg.blockDim = dim3(NTHREADS);
    cfg.dynamicSmemBytes = SMEM_BYTES;
    cfg.stream = cudaStreamPerThread;
    cudaLaunchAttribute at[1];
    at[0].id = cudaLaunchAttributeClusterDimension;
    at[0].val.clusterDim.x = CL; at[0].val.clusterDim.y = 1; at[0].val.clusterDim.z = 1;
    cfg.attrs = at;
    cfg.numAttrs = 1;
    cudaLaunchKernelEx(&cfg, adaln_attn_mlp_decode_kernel, maps, p);
}
```

```cpp
#include <cuda_runtime.h>
#include <cuda_bf16.h>
#include <cuda.h>
#include <stdint.h>

namespace {

constexpr int SK_ = 65536, WIN_ = 4096, F_ = 4608;
constexpr int CL = 6, NCL = 16, NCTA = CL * NCL, NTHREADS = 288;
constexpr int NP1 = 32;

constexpr int P_KV = 14, N_ITEMS = 14 + 44 + 6 + 9 + 9;
constexpr int BAR_CK = N_ITEMS;
constexpr int BAR_CV = BAR_CK + 22;
constexpr int BAR_DQ = BAR_CV + 22;
constexpr int BAR_DS = BAR_DQ + 1, BAR_DO = BAR_DQ + 2, BAR_DX = BAR_DQ + 3, BAR_DH = BAR_DQ + 4;
constexpr int N_BARS = BAR_DQ + 5;
__host__ __device__ constexpr int pos_a(int j) { return j + (j + 1) / 2; }
__host__ __device__ constexpr int pos_b(int j) { return 1 + 3 * j; }

constexpr int OFF_WOA = 0;
constexpr int OFF_WOB = 32768;
constexpr int OFF_W1A = 49152;
constexpr int OFF_W1B = OFF_W1A + 49152;
constexpr int OFF_W2A = OFF_W1B + 6144;
constexpr int OFF_W2B = OFF_W2A + 36864;
constexpr int OFF_M = 0;
constexpr int OFF_Q = 46080;
constexpr int OFF_X = 95232;
constexpr int OFF_SMALL = OFF_X + 14 * 8192;
constexpr int S_BARS = OFF_SMALL;
constexpr int S_H = S_BARS + 1088;
constexpr int S_X = S_H + 192;
constexpr int S_IN = S_X + 2304;
constexpr int S_QS = S_IN + 6912;
constexpr int S_P = S_QS + 512;
constexpr int S_PART = S_P + 2848;
constexpr int S_RED = S_PART + 3072;
constexpr int S_ST = S_RED + 256;
constexpr int S_F = S_ST + 96;
constexpr int S_HV = S_F + 64;
constexpr int S_G = S_HV + 576;
constexpr int S_MISC = S_G + 1536;
constexpr int S_DESC = S_MISC + 32;
constexpr int SMEM_BYTES = S_DESC + 384;
static_assert(N_BARS * 8 <= 1088, "barriers");
static_assert(OFF_W2B + 18432 <= OFF_X + 8 * 8192, "late weights");
static_assert(SMEM_BYTES <= 232448, "smem");
constexpr int PROW = 712;

#define RATE_KV 3240.0f
#define RATE_LATE 3300.0f
#define WIN_KV 8
#define WIN_LATE 8
#define WIN_L6 8
#define NFIRST 4
#define LATE_FROM 18
#define P1_Q_STEP 150.0f
#define DELAY_G1 950
#define GAP_G1 0
#define GAP_G2 0
#define DELAY_G2 280
constexpr float BYTES_22 = 46080.f + 49152.f + 44 * 8192.f + 49152.f + 55296.f + 55296.f;
constexpr float BYTES_21 = BYTES_22 - 2 * 8192.f;
constexpr float BYTES_ALL = 2 * NCL * BYTES_22 + 4 * NCL * BYTES_21;

#define T_RATE_KV RATE_KV
#define T_RATE_LATE RATE_LATE
#define T_WIN_KV WIN_KV
#define T_WIN_LATE WIN_LATE
#define T_LATE_FROM LATE_FROM
#define T_WIN_L6 WIN_L6
#define T_GAP_G1 GAP_G1
#define T_GAP_G2 GAP_G2
#define T_P1_Q_STEP P1_Q_STEP
#define T_DELAY_G1 DELAY_G1
#define T_DELAY_G2 DELAY_G2

struct Maps { CUtensorMap wmod, wq, k, v, woa, wob, w1a, w1b, w2a, w2b; };
struct Ptrs {
    const __nv_bfloat16 *x, *c;
    __nv_bfloat16* out;
};

constexpr int MB_MOD = 0;
constexpr int MB_P1 = MB_MOD + NCTA * 40;
constexpr int MB_P2 = MB_P1 + NCTA * 96;
constexpr int MB_END = MB_P2 + NCTA * 96;
__device__ __align__(128) uint32_t g_mail[MB_END];
__device__ uint32_t g_count;

__device__ __forceinline__ uint32_t smem_u32(const void* p) { return (uint32_t)__cvta_generic_to_shared(p); }
__device__ __forceinline__ void mbar_init(uint32_t bar, uint32_t cnt) {
    asm volatile("mbarrier.init.shared::cta.b64 [%0], %1;" ::"r"(bar), "r"(cnt));
}
__device__ __forceinline__ void mbar_expect_tx(uint32_t bar, uint32_t bytes) {
    asm volatile("mbarrier.arrive.expect_tx.shared::cta.b64 _, [%0], %1;" ::"r"(bar), "r"(bytes) : "memory");
}
__device__ __forceinline__ void mbar_arrive(uint32_t bar) {
    asm volatile("mbarrier.arrive.shared::cta.b64 _, [%0];" ::"r"(bar) : "memory");
}
constexpr int SPIN_LIMIT = 1 << 18;
__device__ __forceinline__ uint32_t mbar_try(uint32_t bar) {
    uint32_t ok;
    asm volatile("{\n.reg .pred p;\nmbarrier.try_wait.parity.shared::cta.b64 p, [%1], 0;\nselp.u32 %0, 1, 0, p;\n}"
                 : "=r"(ok) : "r"(bar) : "memory");
    return ok;
}
__device__ __forceinline__ uint32_t mbar_test(uint32_t bar) {
    uint32_t ok;
    asm volatile("{\n.reg .pred p;\nmbarrier.test_wait.parity.shared::cta.b64 p, [%1], 0;\nselp.u32 %0, 1, 0, p;\n}"
                 : "=r"(ok) : "r"(bar) : "memory");
    return ok;
}
__device__ __forceinline__ void mbar_wait(uint32_t bar) {
    int it = 0;
    while (!mbar_try(bar) && ++it < SPIN_LIMIT) {}
}
__device__ __forceinline__ void mbar_wait2(uint32_t bar0, uint32_t bar1) {
    int it = 0;
    while (!(mbar_try(bar0) & mbar_try(bar1)) && ++it < SPIN_LIMIT) {}
}
__device__ __forceinline__ void mbar_wait_cl(uint32_t bar) {
    uint32_t ok;
    int it = 0;
    do {
        asm volatile("{\n.reg .pred p;\nmbarrier.try_wait.parity.acquire.cluster.shared::cta.b64 p, [%1], 0;\nselp.u32 %0, 1, 0, p;\n}"
                     : "=r"(ok) : "r"(bar) : "memory");
    } while (!ok && ++it < SPIN_LIMIT);
}
__device__ __forceinline__ uint32_t mapa(uint32_t a, uint32_t rank) {
    uint32_t d;
    asm("mapa.shared::cluster.u32 %0, %1, %2;" : "=r"(d) : "r"(a), "r"(rank));
    return d;
}
__device__ __forceinline__ void st_async1(uint32_t dst, uint32_t v, uint32_t bar) {
    asm volatile("st.async.weak.shared::cluster.mbarrier::complete_tx::bytes.b32 [%0], %1, [%2];" ::"r"(dst), "r"(v), "r"(bar) : "memory");
}
__device__ __forceinline__ void st_async4(uint32_t dst, float a, float b, float c, float d, uint32_t bar) {
    asm volatile("st.async.weak.shared::cluster.mbarrier::complete_tx::bytes.v4.f32 [%0], {%1, %2, %3, %4}, [%5];"
                 ::"r"(dst), "f"(a), "f"(b), "f"(c), "f"(d), "r"(bar) : "memory");
}
__device__ __forceinline__ void bcast_word(const uint32_t (&rb)[CL], uint32_t off, uint32_t v, uint32_t bar_off) {
#pragma unroll
    for (int d = 0; d < CL; d++) st_async1(rb[d] + off, v, rb[d] + bar_off);
}
__device__ __forceinline__ void tma2d(uint32_t dst, const CUtensorMap* m, int c0, int c1, uint32_t bar) {
    asm volatile("cp.async.bulk.tensor.2d.shared::cluster.global.mbarrier::complete_tx::bytes [%0], [%1, {%3, %4}], [%2];"
                 ::"r"(dst), "l"(m), "r"(bar), "r"(c0), "r"(c1) : "memory");
}
__device__ __forceinline__ void tma3d(uint32_t dst, const CUtensorMap* m, int c0, int c1, int c2, uint32_t bar, uint64_t pol) {
    asm volatile("cp.async.bulk.tensor.3d.shared::cluster.global.mbarrier::complete_tx::bytes.L2::cache_hint [%0], [%1, {%3, %4, %5}], [%2], %6;"
                 ::"r"(dst), "l"(m), "r"(bar), "r"(c0), "r"(c1), "r"(c2), "l"(pol) : "memory");
}
__device__ __forceinline__ void issue2d(uint32_t bar, uint32_t bytes, uint32_t dst, const CUtensorMap* m, int c0, int c1) {
    asm volatile("{\n.reg .pred p;\nelect.sync _|p, 0xffffffff;\n"
                 "@p mbarrier.arrive.expect_tx.shared::cta.b64 _, [%0], %1;\n"
                 "@p cp.async.bulk.tensor.2d.shared::cluster.global.mbarrier::complete_tx::bytes [%2], [%3, {%4, %5}], [%0];\n}"
                 ::"r"(bar), "r"(bytes), "r"(dst), "l"(m), "r"(c0), "r"(c1) : "memory");
}
__device__ __forceinline__ void issue3d(uint32_t bar, uint32_t dst, const CUtensorMap* m, int row, uint64_t pol) {
    asm volatile("{\n.reg .pred p;\nelect.sync _|p, 0xffffffff;\n"
                 "@p mbarrier.arrive.expect_tx.shared::cta.b64 _, [%0], 8192;\n"
                 "@p cp.async.bulk.tensor.3d.shared::cluster.global.mbarrier::complete_tx::bytes.L2::cache_hint [%1], [%2, {0, %3, 0}], [%0], %4;\n}"
                 ::"r"(bar), "r"(dst), "l"(m), "r"(row), "l"(pol) : "memory");
}
__device__ __forceinline__ void ldsm4(uint32_t (&r)[4], uint32_t a) {
    asm volatile("ldmatrix.sync.aligned.m8n8.x4.shared.b16 {%0, %1, %2, %3}, [%4];"
                 : "=r"(r[0]), "=r"(r[1]), "=r"(r[2]), "=r"(r[3]) : "r"(a) : "memory");
}
__device__ __forceinline__ void ldsm4t(uint32_t (&r)[4], uint32_t a) {
    asm volatile("ldmatrix.sync.aligned.m8n8.x4.trans.shared.b16 {%0, %1, %2, %3}, [%4];"
                 : "=r"(r[0]), "=r"(r[1]), "=r"(r[2]), "=r"(r[3]) : "r"(a) : "memory");
}
__device__ __forceinline__ void mma16816(float (&c)[4], const uint32_t (&a)[4], uint32_t b0, uint32_t b1) {
    asm volatile("mma.sync.aligned.m16n8k16.row.col.f32.bf16.bf16.f32 {%0, %1, %2, %3}, {%4, %5, %6, %7}, {%8, %9}, {%0, %1, %2, %3};"
                 : "+f"(c[0]), "+f"(c[1]), "+f"(c[2]), "+f"(c[3])
                 : "r"(a[0]), "r"(a[1]), "r"(a[2]), "r"(a[3]), "r"(b0), "r"(b1));
}
__device__ __forceinline__ uint32_t lds32(uint32_t a) {
    uint32_t v;
    asm volatile("ld.shared.b32 %0, [%1];" : "=r"(v) : "r"(a) : "memory");
    return v;
}
__device__ __forceinline__ void cbar() { asm volatile("bar.sync 1, 256;" ::: "memory"); }

__device__ __forceinline__ void st_word(uint32_t* p, uint32_t v) {
    asm volatile("st.relaxed.gpu.global.b32 [%0], %1;" ::"l"(p), "r"(v) : "memory");
}
__device__ __forceinline__ uint4 ld_pkt(const uint32_t* p) {
    uint4 v;
    asm volatile("ld.relaxed.gpu.global.v4.b32 {%0, %1, %2, %3}, [%4];"
                 : "=r"(v.x), "=r"(v.y), "=r"(v.z), "=r"(v.w) : "l"(p) : "memory");
    return v;
}
__device__ __forceinline__ bool pkt_ok(const uint4& v, uint32_t tag) {
    return (((v.x ^ tag) | (v.y ^ tag) | (v.z ^ tag) | (v.w ^ tag)) & 3u) == 0u;
}
__device__ __forceinline__ void spin_cycles(uint32_t n) {
    uint32_t c0, c1;
    asm volatile("mov.u32 %0, %%clock;" : "=r"(c0));
    do { asm volatile("mov.u32 %0, %%clock;" : "=r"(c1)); } while (c1 - c0 < n);
}
__device__ __forceinline__ uint4 poll_pkt(const uint32_t* p, uint32_t tag) {
    uint4 v;
    int it = 0;
    do { v = ld_pkt(p); } while (!pkt_ok(v, tag) && ++it < SPIN_LIMIT);
    return v;
}
__device__ __forceinline__ void poll_pkt2(const uint32_t* p, const uint32_t* q, uint32_t tag, uint4& v, uint4& w) {
    int it = 0;
    do { v = ld_pkt(p); w = ld_pkt(q); } while (!(pkt_ok(v, tag) && pkt_ok(w, tag)) && ++it < SPIN_LIMIT);
}
__device__ __forceinline__ uint4 poll_pkt_x2(const uint32_t* p, uint32_t tag, uint32_t gap) {
    uint4 a = ld_pkt(p);
    spin_cycles(gap);
    uint4 c = ld_pkt(p);
    for (int it = 0; it < SPIN_LIMIT; it++) {
        if (pkt_ok(a, tag)) return a;
        a = ld_pkt(p);
        if (pkt_ok(c, tag)) return c;
        c = ld_pkt(p);
    }
    return a;
}
__device__ __forceinline__ void poll_pkt2_x2(const uint32_t* p, const uint32_t* q, uint32_t tag, uint32_t gap, uint4& v, uint4& w) {
    uint4 a0 = ld_pkt(p), a1 = ld_pkt(q);
    spin_cycles(gap);
    uint4 c0 = ld_pkt(p), c1 = ld_pkt(q);
    for (int it = 0; it < SPIN_LIMIT; it++) {
        if (pkt_ok(a0, tag) && pkt_ok(a1, tag)) { v = a0; w = a1; return; }
        a0 = ld_pkt(p); a1 = ld_pkt(q);
        if (pkt_ok(c0, tag) && pkt_ok(c1, tag)) { v = c0; w = c1; return; }
        c0 = ld_pkt(p); c1 = ld_pkt(q);
    }
    v = a0; w = a1;
}
__device__ __forceinline__ uint32_t pack2(float lo, float hi) {
    uint32_t u;
    asm("cvt.rn.bf16x2.f32 %0, %1, %2;" : "=r"(u) : "f"(hi), "f"(lo));
    return u;
}
__device__ __forceinline__ float rbf(float x) { return __uint_as_float(pack2(0.f, x)); }
__device__ __forceinline__ float ex2(float x) { float y; asm("ex2.approx.ftz.f32 %0, %1;" : "=f"(y) : "f"(x)); return y; }
__device__ __forceinline__ float rcp(float x) { float y; asm("rcp.approx.ftz.f32 %0, %1;" : "=f"(y) : "f"(x)); return y; }
__device__ __forceinline__ float sqrt_a(float x) { float y; asm("sqrt.approx.ftz.f32 %0, %1;" : "=f"(y) : "f"(x)); return y; }
constexpr float LOG2E = 1.4426950408889634f;
__device__ __forceinline__ uint32_t word_bf(float x_rounded, uint32_t tag) { return __float_as_uint(x_rounded) | tag; }
__device__ __forceinline__ uint32_t word_f32(float x, uint32_t tag) { return (__float_as_uint(x) & ~3u) | tag; }
__device__ __forceinline__ float unword(uint32_t w) { return __uint_as_float(w & ~3u); }
__device__ __forceinline__ float bf_lo(uint32_t w) { return __uint_as_float(w << 16); }
__device__ __forceinline__ float bf_hi(uint32_t w) { return __uint_as_float(w & 0xFFFF0000u); }
__device__ __forceinline__ uint32_t pack_hi(uint32_t a, uint32_t b) { return __byte_perm(a, b, 0x7632); }
__device__ __forceinline__ uint32_t gtime() { unsigned long long t; asm volatile("mov.u64 %0, %%globaltimer;" : "=l"(t)); return (uint32_t)t; }
__device__ __forceinline__ int mod_word(int c) { const int pb = c / 36; return MB_MOD + pb * 40 + (c - pb * 36); }

template <int LO, int HI>
__device__ __forceinline__ void init_bars(uint32_t bars) {
#pragma unroll
    for (int i = LO; i < HI; i++) mbar_init(bars + 8 * i, (i >= BAR_CV && i < BAR_DQ) ? 8 : 1);
}

#define STAMP(i)
#define PSTAMP(i)

__device__ __forceinline__ void ln_stats(const float* xs, int lane, float& mean_b, float& inv_den) {
    float v[18];
    const float c = xs[0];
#pragma unroll
    for (int i = 0; i < 4; i++) {
        const float4 a = *reinterpret_cast<const float4*>(xs + i * 128 + lane * 4);
        v[4 * i] = a.x; v[4 * i + 1] = a.y; v[4 * i + 2] = a.z; v[4 * i + 3] = a.w;
    }
    {
        const float2 a = *reinterpret_cast<const float2*>(xs + 512 + lane * 2);
        v[16] = a.x; v[17] = a.y;
    }
    float s0 = 0.f, s1 = 0.f, s2 = 0.f, q0 = 0.f, q1 = 0.f, q2 = 0.f;
#pragma unroll
    for (int i = 0; i < 18; i += 3) {
        const float d0 = v[i] - c, d1 = v[i + 1] - c, d2 = v[i + 2] - c;
        s0 += d0; s1 += d1; s2 += d2;
        q0 = fmaf(d0, d0, q0); q1 = fmaf(d1, d1, q1); q2 = fmaf(d2, d2, q2);
    }
    float s = (s0 + s1) + s2, q = (q0 + q1) + q2;
#pragma unroll
    for (int o = 16; o > 0; o >>= 1) {
        s += __shfl_xor_sync(0xffffffffu, s, o);
        q += __shfl_xor_sync(0xffffffffu, q, o);
    }
    const float md = s * (1.0f / 576.0f);
    const float var = fmaxf(fmaf(-md, md, q * (1.0f / 576.0f)), 0.f);
    mean_b = rbf(c + md);
    inv_den = rcp(rbf(sqrt_a(rbf(rbf(var) + 1e-5f))));
}

__device__ __forceinline__ void ld_vec2(uint32_t (&b)[4], uint32_t v, int j, int mi) { ldsm4(b, v + (4 * j + mi) * 16); }

__device__ __forceinline__ void ld_ntile(uint32_t (&a)[6][4], uint32_t base_a, uint32_t base_b, int row0, int mi, int l7) {
    const int row = row0 + (mi >> 1) * 8 + l7;
    const uint32_t ra = base_a + row * 128, rb = base_b + row * 64;
#pragma unroll
    for (int m = 0; m < 4; m++) ldsm4t(a[m], ra + (((2 * m + (mi & 1)) ^ l7) << 4));
#pragma unroll
    for (int m = 0; m < 2; m++) ldsm4t(a[4 + m], rb + (((2 * m + (mi & 1)) ^ ((row >> 1) & 3)) << 4));
}

__global__ void __launch_bounds__(NTHREADS, 1)
adaln_attn_mlp_decode_kernel(const __grid_constant__ Maps maps, const Ptrs p) {
    extern __shared__ __align__(1024) uint8_t sm[];
    const uint32_t sb = smem_u32(sm);
    int tid, b, r;
    asm volatile("mov.u32 %0, %%tid.x;" : "=r"(tid));
    asm volatile("mov.u32 %0, %%ctaid.x;" : "=r"(b));
    asm volatile("mov.u32 %0, %%cluster_ctarank;" : "=r"(r));
    const int g = b / CL;
    const int nt = 21 + (r < 2);
    const uint32_t bars = sb + S_BARS;
    const int pos_m = b < NP1 ? 0 : 8, pos_q = b < NP1 ? 6 : 0;
    const int pos_o = P_KV + 2 * nt, pos_w1 = pos_o + 6, pos_w2 = pos_w1 + 9;

    uint32_t t0 = 0;
    if (tid == 256) {
        t0 = gtime();
        PSTAMP(16);
        if (sb & 1023u) __trap();
        init_bars<0, P_KV>(bars);
        asm volatile("fence.proxy.async.shared::cta;" ::: "memory");
        if (b < NP1) {
#pragma unroll
            for (int i = 0; i < 6; i++) {
                mbar_expect_tx(bars + 8 * i, 7680);
                tma2d(sb + OFF_M + i * 7680, &maps.wmod, b * 36 - (b & 1) * 4, i * 96, bars + 8 * i);
            }
        } else {
#pragma unroll
            for (int i = 0; i < NFIRST; i++) {
                mbar_expect_tx(bars + 8 * i, 6144);
                tma2d(sb + OFF_Q + i * 6144, &maps.wq, g * 256 + (i >> 1) * 64, r * 96 + (i & 1) * 48, bars + 8 * i);
            }
        }
    }

    if (tid >= 256) {
        if (tid > 256 && tid <= 256 + 24) {
            const int i = tid - 257;
            const int ca = r * 96 + (r & 1) * 32, cb = r * 96 + ((r & 1) ? 0 : 64);
            const int c1a = g * 288 + (g & 1) * 32, c1b = g * 288 + ((g & 1) ? 0 : 256);
            uint32_t dst, map; int c0, c1;
            if (i < 6) {
                const bool isb = (i == 1 || i == 4);
                const int j = isb ? (i >> 2) : (i == 0 ? 0 : (i == 5 ? 3 : i - 1));
                dst = isb ? OFF_WOB + j * 8192 : OFF_WOA + j * 8192; map = isb ? 5 : 4;
                c0 = isb ? cb : ca; c1 = g * 256 + j * (isb ? 128 : 64);
            } else if (i < 15) {
                const int j = i - 6;
                dst = j < 8 ? OFF_W1A + j * 6144 : OFF_W1B; map = j < 8 ? 6 : 7;
                c0 = j < 8 ? c1a + (j >> 1) * 64 : c1b; c1 = r * 96 + (j < 8 ? (j & 1) * 48 : 0);
            } else {
                const int k = i - 15, q = k / 3, m = k - 3 * q;
                const bool isb = m == 1;
                const int j = isb ? q : 2 * q + (m == 2);
                dst = isb ? OFF_W2B + j * 6144 : OFF_W2A + j * 6144; map = isb ? 9 : 8;
                c0 = isb ? cb : ca; c1 = g * 288 + j * (isb ? 96 : 48);
            }
            *reinterpret_cast<uint4*>(sm + S_DESC + i * 16) = make_uint4(sb + dst, map * 128u, (uint32_t)c0, (uint32_t)c1);
        }
        __syncwarp();
        asm volatile("bar.arrive 2, 288;" ::: "memory");
        asm volatile("barrier.cluster.arrive.relaxed.aligned;" ::: "memory");
        uint64_t pol;
        asm volatile("createpolicy.fractional.L2::evict_first.b64 %0, 1.0;" : "=l"(pol));
        const float nsb_kv = (r < 2 ? BYTES_ALL / BYTES_22 : BYTES_ALL / BYTES_21) * __frcp_rn(T_RATE_KV);
        const float nsb_late = (r < 2 ? BYTES_ALL / BYTES_22 : BYTES_ALL / BYTES_21) * __frcp_rn(T_RATE_LATE);
        t0 = __shfl_sync(0xffffffffu, t0, 0);
        uint32_t tn = 0;
        uint32_t bar = bars;
        auto gate = [&](uint32_t wbar, uint32_t t) {
            uint32_t now = gtime();
            mbar_wait(wbar);
            for (int it = 0; now - t0 < t && it < SPIN_LIMIT; it++) now = gtime();
        };
        auto gate2 = [&](uint32_t wbar, uint32_t dep, uint32_t t) {
            uint32_t now = gtime();
            mbar_wait2(wbar, dep);
            for (int it = 0; now - t0 < t && it < SPIN_LIMIT; it++) now = gtime();
        };
#define ITEMLOG()
        {
            const uint32_t st_m = (uint32_t)(7680.f * nsb_kv), st_q = (uint32_t)(6144.f * nsb_kv);
            const int q0 = b < NP1 ? 0 : NFIRST;
            bar += 8 * (b < NP1 ? 6 : NFIRST);
            tn += b < NP1 ? 6 * st_m : NFIRST * st_q;
#pragma unroll 1
            for (int i = q0; i < 8; i++) {
                const uint32_t wb = bar >= bars + 8 * T_WIN_KV ? bar - 8 * T_WIN_KV : bar;
                const uint32_t t = b < NP1 ? (uint32_t)T_P1_Q_STEP * (i + 1) : tn;
                if (wb != bar) gate(wb, t); else for (int it = 0; gtime() - t0 < t && it < SPIN_LIMIT; it++) {}
                ITEMLOG();
                issue2d(bar, 6144, sb + OFF_Q + i * 6144, &maps.wq, g * 256 + (i >> 1) * 64, r * 96 + (i & 1) * 48);
                bar += 8; tn += st_q;
            }
            if (b >= NP1) {
#pragma unroll 1
                for (int i = 0; i < 6; i++) {
                    gate(bar >= bars + 8 * T_WIN_KV ? bar - 8 * T_WIN_KV : bars, tn);
                    ITEMLOG();
                    issue2d(bar, 7680, sb + OFF_M + i * 7680, &maps.wmod, b * 36 - (b & 1) * 4, i * 96);
                    bar += 8; tn += st_m;
                }
            }
        }
        asm volatile("bar.sync 3, 288;" ::: "memory");
        {
            const uint32_t st_kv = (uint32_t)(8192.f * nsb_kv), st_late8 = (uint32_t)(8192.f * nsb_late), st_late6 = (uint32_t)(6144.f * nsb_late);
            const int row0 = g * SK_ + (SK_ - WIN_) + (21 * r + (r < 2 ? r : 2)) * 32;
            uint32_t dst = sb + OFF_X + 12 * 8192;
            int row = row0;
#pragma unroll 1
            for (int i = 0; i < 14; i++) {
                gate(bar - 8 * T_WIN_KV, tn);
                ITEMLOG();
                issue3d(bar, dst, &maps.k, row, pol);
                bar += 8; tn += st_kv; row += 32;
                dst += 8192; if (dst == sb + OFF_X + 14 * 8192) dst = sb + OFF_X;
            }
            uint32_t cons = bars + 8 * BAR_CK;
#pragma unroll 1
            for (int i = 14; i < nt; i++) {
                gate2(bar - 8 * T_WIN_KV, cons, tn);
                ITEMLOG();
                issue3d(bar, dst, &maps.k, row, pol);
                bar += 8; cons += 8; tn += st_kv; row += 32;
                dst += 8192; if (dst == sb + OFF_X + 14 * 8192) dst = sb + OFF_X;
            }
            if (tid == 256) PSTAMP(17);
            row = row0;
#pragma unroll 1
            for (int i = 0; i < nt; i++) {
                const bool late = i >= T_LATE_FROM;
                if (i == 14) cons = bars + 8 * BAR_CV;
                gate2(bar - 8 * (late ? T_WIN_LATE : T_WIN_KV), cons, tn);
                ITEMLOG();
                issue3d(bar, dst, &maps.v, row, pol);
                bar += 8; cons += 8; tn += late ? st_late8 : st_kv; row += 32;
                dst += 8192; if (dst == sb + OFF_X + 14 * 8192) dst = sb + OFF_X;
            }
            if (tid == 256) PSTAMP(18);
            const uint32_t cv = bars + 8 * (BAR_CV + 30 - nt);
            const uint8_t* const mbase = reinterpret_cast<const uint8_t*>(&maps);
#pragma unroll 1
            for (int i = 0; i < 24; i++) {
                const uint4 d = *reinterpret_cast<const uint4*>(sm + S_DESC + i * 16);
                if (i == 13) mbar_wait2(cv, cv + 8);
                if (i == 15) { mbar_wait2(cv + 16, cv + 24); mbar_wait2(cv + 32, cv + 40); mbar_wait2(cv + 48, cv + 56); }
                gate(bar - 8 * (i < 6 ? T_WIN_LATE : T_WIN_L6), tn);
                ITEMLOG();
                issue2d(bar, i < 6 ? 8192 : 6144, d.x, reinterpret_cast<const CUtensorMap*>(mbase + d.y), (int)d.z, (int)d.w);
                bar += 8; tn += i < 6 ? st_late8 : st_late6;
            }
            if (tid == 256) PSTAMP(19);
        }
        return;
    }

    const int lane = tid & 31, wid = tid >> 5;
    const int gq = lane >> 2, t4 = lane & 3;
    const int mi = lane >> 3, l7 = lane & 7;
    float* const xs = reinterpret_cast<float*>(sm + S_X);
    float* const part = reinterpret_cast<float*>(sm + S_PART);
    float* const red = reinterpret_cast<float*>(sm + S_RED);
    float* const inbox = reinterpret_cast<float*>(sm + S_IN);
    uint32_t* mail;
    asm volatile("mov.u64 %0, %1;" : "=l"(mail) : "l"(g_mail));
    STAMP(0);

    uint4 ldv = make_uint4(0u, 0u, 0u, 0u);
    if (tid < 72) ldv = *reinterpret_cast<const uint4*>(p.x + tid * 8);
    else if (tid >= 128 && tid < 200) ldv = *reinterpret_cast<const uint4*>(p.c + (tid - 128) * 8);
    else if (tid == 255) asm volatile("ld.relaxed.gpu.global.b32 %0, [%1];" : "=r"(ldv.x) : "l"(&g_count) : "memory");
    if (lane == 0) {
        constexpr int NB = N_BARS - P_KV, Q = (NB + 7) / 8;
        switch (wid) {
            case 0: init_bars<P_KV + 0 * Q, P_KV + 1 * Q>(bars); break;
            case 1: init_bars<P_KV + 1 * Q, P_KV + 2 * Q>(bars); break;
            case 2: init_bars<P_KV + 2 * Q, P_KV + 3 * Q>(bars); break;
            case 3: init_bars<P_KV + 3 * Q, P_KV + 4 * Q>(bars); break;
            case 4: init_bars<P_KV + 4 * Q, P_KV + 5 * Q>(bars); break;
            case 5: init_bars<P_KV + 5 * Q, P_KV + 6 * Q>(bars); break;
            case 6: init_bars<P_KV + 6 * Q, P_KV + 7 * Q>(bars); break;
            default:
                init_bars<P_KV + 7 * Q, N_BARS>(bars);
                static_assert(P_KV + 7 * Q <= BAR_DQ, "the last warp arms the exchange barriers");
                mbar_expect_tx(bars + 8 * BAR_DQ, CL * 1024);
                mbar_expect_tx(bars + 8 * BAR_DS, CL * 16);
                mbar_expect_tx(bars + 8 * BAR_DO, CL * 1024);
                mbar_expect_tx(bars + 8 * BAR_DX, CL * 384);
                mbar_expect_tx(bars + 8 * BAR_DH, CL * 1152);
                break;
        }
        asm volatile("fence.mbarrier_init.release.cluster;" ::: "memory");
        asm volatile("fence.proxy.async.shared::cta;" ::: "memory");
    }
    __syncwarp();
    asm volatile("bar.arrive 3, 288;" ::: "memory");
    asm volatile("barrier.cluster.arrive.relaxed.aligned;" ::: "memory");
    if (tid < 96) { st_word(mail + MB_P1 + b * 96 + tid, 0u); st_word(mail + MB_P2 + b * 96 + tid, 0u); }
    if (tid >= 96 && tid < 136) st_word(mail + MB_MOD + b * 40 + tid - 96, 0u);
    if (tid < 72) {
        *reinterpret_cast<float4*>(xs + tid * 8) = make_float4(bf_lo(ldv.x), bf_hi(ldv.x), bf_lo(ldv.y), bf_hi(ldv.y));
        *reinterpret_cast<float4*>(xs + tid * 8 + 4) = make_float4(bf_lo(ldv.z), bf_hi(ldv.z), bf_lo(ldv.w), bf_hi(ldv.w));
    } else if (tid >= 128 && tid < 200) {
        const uint32_t w[4] = {ldv.x, ldv.y, ldv.z, ldv.w};
        uint32_t o[4];
#pragma unroll
        for (int j = 0; j < 4; j++) {
            const float lo = bf_lo(w[j]), hi = bf_hi(w[j]);
            o[j] = pack2(lo * rcp(1.0f + ex2(-lo * LOG2E)), hi * rcp(1.0f + ex2(-hi * LOG2E)));
        }
        *reinterpret_cast<uint4*>(sm + S_P + (tid - 128) * 16) = make_uint4(o[0], o[1], o[2], o[3]);
    } else if (tid == 255) {
        reinterpret_cast<uint32_t*>(sm + S_MISC)[0] = ldv.x;
    }
    asm volatile("bar.sync 2, 288;" ::: "memory");
    const uint32_t cnt = reinterpret_cast<const uint32_t*>(sm + S_MISC)[0];
    const uint32_t tag = 1u + cnt;

    const int pc = (wid < 6 ? wid : 0) * 4 + t4;
    const float4 xown = *reinterpret_cast<const float4*>(xs + r * 96 + pc * 4);
    float xn[4] = {0.f, 0.f, 0.f, 0.f};
    if (wid == 0) {
        float mean_b, inv_den;
        ln_stats(xs, lane, mean_b, inv_den);
        const float4 v = *reinterpret_cast<const float4*>(xs + r * 96 + (lane < 24 ? lane : 0) * 4);
        xn[0] = rbf(rbf(v.x - mean_b) * inv_den); xn[1] = rbf(rbf(v.y - mean_b) * inv_den);
        xn[2] = rbf(rbf(v.z - mean_b) * inv_den); xn[3] = rbf(rbf(v.w - mean_b) * inv_den);
    }
    asm volatile("barrier.cluster.wait.acquire.aligned;" ::: "memory");

    uint32_t rb[CL];
#pragma unroll
    for (int d = 0; d < CL; d++) rb[d] = mapa(sb, d);
    const int ca_off = (r & 1) * 32, cb_off = (r & 1) ? 0 : 64;
    const int cm_w = wid < 4 ? wid * 16 + ca_off : (wid - 4) * 16 + cb_off;
    float acc[6][4];
#pragma unroll 1
    for (int ph = 0; ph < 2; ph++) {
        if ((ph == 0) == (b < NP1)) {
#pragma unroll
            for (int m = 0; m < 3; m++) { acc[m][0] = acc[m][1] = acc[m][2] = acc[m][3] = 0.f; }
            const uint32_t base = sb + OFF_M + (wid * 16 + (mi >> 1) * 8 + l7) * 80 + (mi & 1) * 16;
#pragma unroll
            for (int i = 0; i < 5; i++) {
                const int s = wid + 8 * i;
                if (i < 4 || wid < 4) {
                    const uint32_t b0 = lds32(sb + S_P + (s * 16 + 2 * t4) * 2), b1 = lds32(sb + S_P + (s * 16 + 8 + 2 * t4) * 2);
                    mbar_wait(bars + 8 * (pos_m + s / 6));
#pragma unroll
                    for (int m = 0; m < 3; m++) {
                        uint32_t a[4];
                        ldsm4t(a, base + i * (128 * 80) + m * 32);
                        mma16816(acc[m], a, b0, b1);
                    }
                }
            }
            if (t4 == 0) {
#pragma unroll
                for (int m = 0; m < 3; m++) { part[wid * 48 + m * 16 + gq] = acc[m][0]; part[wid * 48 + m * 16 + 8 + gq] = acc[m][2]; }
            }
            cbar();
            if (tid < 40) {
                const float* pp = part + tid;
                float m = rbf(((pp[0] + pp[48]) + (pp[96] + pp[144])) + ((pp[192] + pp[240]) + (pp[288] + pp[336])));
                const int u = tid - (b & 1) * 4;
                const int col = b * 36 + u;
                if ((col >= 576 && col < 1152) || (col >= 2304 && col < 2880)) m = rbf(1.0f + m);
                st_word(mail + MB_MOD + b * 40 + (u >= 0 && u < 36 ? u : (u < 0 ? u + 40 : u)), word_bf(m, tag));
            }
            STAMP(1);
            cbar();
        }
        if (ph == 1) break;

        if (tid < 24) {
            uint4 sa, ca;
            poll_pkt2(mail + mod_word(r * 96 + tid * 4), mail + mod_word(576 + r * 96 + tid * 4), tag, sa, ca);
            const float h0 = rbf(xn[0] * bf_hi(ca.x)) + bf_hi(sa.x), h1 = rbf(xn[1] * bf_hi(ca.y)) + bf_hi(sa.y);
            const float h2 = rbf(xn[2] * bf_hi(ca.z)) + bf_hi(sa.z), h3 = rbf(xn[3] * bf_hi(ca.w)) + bf_hi(sa.w);
            *reinterpret_cast<uint2*>(sm + S_H + tid * 8) = make_uint2(pack2(h0, h1), pack2(h2, h3));
        }
        cbar();
        STAMP(2);

        const int cb = wid >> 1;
        mbar_wait2(bars + 8 * (pos_q + 2 * cb), bars + 8 * (pos_q + 2 * cb + 1));
        float c0[4] = {0.f, 0.f, 0.f, 0.f}, c1[4] = {0.f, 0.f, 0.f, 0.f};
#pragma unroll
        for (int s = 0; s < 6; s++) {
            const int row = s * 16 + (mi >> 1) * 8 + l7;
            const uint32_t ra = sb + OFF_Q + cb * 12288 + row * 128;
            const int ch = (wid & 1) * 4 + (mi & 1);
            uint32_t a0[4], a1[4];
            ldsm4t(a0, ra + ((ch ^ l7) << 4));
            ldsm4t(a1, ra + (((ch + 2) ^ l7) << 4));
            const uint32_t b0 = lds32(sb + S_H + (s * 16 + 2 * t4) * 2), b1 = lds32(sb + S_H + (s * 16 + 8 + 2 * t4) * 2);
            mma16816(c0, a0, b0, b1);
            mma16816(c1, a1, b0, b1);
        }
        const float v = (t4 & 2) ? ((t4 & 1) ? c1[2] : c1[0]) : ((t4 & 1) ? c0[2] : c0[0]);
        bcast_word(rb, S_IN + (r * 288 + wid * 32 + (t4 >> 1) * 16 + (t4 & 1) * 8 + gq) * 4, __float_as_uint(v), S_BARS + 8 * BAR_DQ);
        STAMP(3);
    }
    mbar_wait_cl(bars + 8 * BAR_DQ);
    {
        const float* in = inbox + tid;
        const float q = ((in[0] + in[288]) + (in[576] + in[864])) + (in[1152] + in[1440]);
        reinterpret_cast<uint16_t*>(sm + S_QS)[tid] = (uint16_t)pack2(q, 0.f);
    }
    cbar();
    STAMP(4);

    float sv[2][4];
    {
        uint32_t qb[8][2];
#pragma unroll
        for (int s = 0; s < 8; s++) {
            qb[s][0] = lds32(sb + S_QS + ((gq & 1) * 128 + s * 16 + 2 * t4) * 2);
            qb[s][1] = lds32(sb + S_QS + ((gq & 1) * 128 + s * 16 + 8 + 2 * t4) * 2);
        }
#pragma unroll
        for (int e = 0; e < 4; e++) sv[0][e] = sv[1][e] = -INFINITY;
#pragma unroll
        for (int i = 0; i < 3; i++) {
            const int j = wid + 8 * i;
            if (j < nt) {
                const int slot = j < 2 ? j + 12 : (j < 16 ? j - 2 : j - 16);
                const uint32_t base = sb + OFF_X + slot * 8192;
                mbar_wait(bars + 8 * (P_KV + j));
                float c[2][4] = {{0.f, 0.f, 0.f, 0.f}, {0.f, 0.f, 0.f, 0.f}};
#pragma unroll
                for (int s = 0; s < 8; s++) {
#pragma unroll
                    for (int m = 0; m < 2; m++) {
                        const int row = m * 16 + (mi & 1) * 8 + l7;
                        const int ch = 2 * (s & 3) + (mi >> 1);
                        uint32_t a[4];
                        ldsm4(a, base + (s >> 2) * 4096 + row * 128 + ((ch ^ l7) << 4));
                        mma16816(c[m], a, qb[s][0], qb[s][1]);
                    }
                }
                __syncwarp();
                if (lane == 0) mbar_arrive(bars + 8 * (BAR_CK + j));
#pragma unroll
                for (int m = 0; m < 2; m++) {
                    if (t4 == ((i * 2 + m) & 3)) {
#pragma unroll
                        for (int e = 0; e < 4; e++) sv[i >> 1][e] = rbf(rbf(c[m][e]) * 0.08838834764831845f);
                    }
                }
            }
        }
    }
    STAMP(5);

    {
        float m0 = fmaxf(fmaxf(sv[0][0], sv[0][2]), fmaxf(sv[1][0], sv[1][2]));
        float m1 = fmaxf(fmaxf(sv[0][1], sv[0][3]), fmaxf(sv[1][1], sv[1][3]));
#pragma unroll
        for (int o = 16; o > 0; o >>= 1) {
            m0 = fmaxf(m0, __shfl_xor_sync(0xffffffffu, m0, o));
            m1 = fmaxf(m1, __shfl_xor_sync(0xffffffffu, m1, o));
        }
        if (lane == 0) { red[wid * 2] = m0; red[wid * 2 + 1] = m1; }
        cbar();
#pragma unroll
        for (int w = 0; w < 8; w++) { m0 = fmaxf(m0, red[w * 2]); m1 = fmaxf(m1, red[w * 2 + 1]); }
        uint16_t* P = reinterpret_cast<uint16_t*>(sm + S_P);
        float l0 = 0.f, l1 = 0.f;
#pragma unroll
        for (int h = 0; h < 2; h++) {
            const int j = wid + 8 * (2 * h + (t4 >> 1));
            if ((h == 0 || t4 < 2) && j < nt) {
                const float e0 = ex2((sv[h][0] - m0) * LOG2E), e1 = ex2((sv[h][1] - m1) * LOG2E);
                const float e2 = ex2((sv[h][2] - m0) * LOG2E), e3 = ex2((sv[h][3] - m1) * LOG2E);
                const int key = j * 32 + (t4 & 1) * 16 + gq;
                const uint32_t p01 = pack2(e0, e1), p23 = pack2(e2, e3);
                P[key] = (uint16_t)p01; P[key + 8] = (uint16_t)p23;
                P[PROW + key] = (uint16_t)(p01 >> 16); P[PROW + key + 8] = (uint16_t)(p23 >> 16);
                l0 += e0 + e2; l1 += e1 + e3;
            }
        }
#pragma unroll
        for (int o = 16; o > 0; o >>= 1) {
            l0 += __shfl_xor_sync(0xffffffffu, l0, o);
            l1 += __shfl_xor_sync(0xffffffffu, l1, o);
        }
        if (lane == 0) { red[16 + wid * 2] = l0; red[16 + wid * 2 + 1] = l1; }
        cbar();
        if (tid < 24) {
            const int dst = tid >> 2, e = tid & 3;
            float l = 0.f;
#pragma unroll
            for (int w = 0; w < 8; w++) l += red[16 + w * 2 + (e >> 1)];
            const float v = (e & 1) ? l : ((e >> 1) ? m1 : m0);
            st_async1(mapa(sb + S_ST + (r * 4 + e) * 4, dst), __float_as_uint(v), mapa(bars + 8 * BAR_DS, dst));
        }
    }
    STAMP(6);

    const uint32_t* modp;
    {
        const int t = tid < 96 ? tid : 0, v = t / 24, j = t - v * 24;
        modp = mail + mod_word((v == 0 ? 1152 : (v == 1 ? 2880 : (v == 2 ? 1728 : 2304))) + r * 96 + j * 4);
    }
    uint4 modw = make_uint4(0u, 0u, 0u, 0u);
    if (tid < 96) modw = ld_pkt(modp);

    {
        float c0[4] = {0.f, 0.f, 0.f, 0.f}, c1[4] = {0.f, 0.f, 0.f, 0.f};
        const uint32_t pb = sb + S_P + (gq & 1) * (PROW * 2) + t4 * 4;
        const int ch = 2 * (wid & 3) + (mi & 1);
        const uint32_t aoff = (wid >> 2) * 4096 + ((mi >> 1) * 8 + l7) * 128 + ((ch ^ l7) << 4);
        int slot = nt + 12 - 28;
#pragma unroll 1
        for (int j = 0; j < nt; j++) {
            const uint32_t base = sb + OFF_X + slot * 8192 + aoff;
            const uint32_t b0 = lds32(pb + j * 64), b1 = lds32(pb + j * 64 + 16);
            const uint32_t b2 = lds32(pb + j * 64 + 32), b3 = lds32(pb + j * 64 + 48);
            mbar_wait(bars + 8 * (P_KV + nt + j));
            uint32_t a0[4], a1[4];
            ldsm4t(a0, base);
            ldsm4t(a1, base + 2048);
            mma16816(c0, a0, b0, b1);
            mma16816(c1, a1, b2, b3);
            __syncwarp();
            if (lane == 0) mbar_arrive(bars + 8 * (BAR_CV + j));
            if (++slot == 14) slot = 0;
            if (j == 12 && wid == 0) {
                mbar_wait_cl(bars + 8 * BAR_DS);
                const int src = lane & 7, hh = (lane >> 3) & 1;
                const float2 st = *reinterpret_cast<const float2*>(sm + S_ST + ((src < CL ? src : 0) * 4 + hh * 2) * 4);
                const float m = src < CL ? st.x : -INFINITY;
                float M = m;
#pragma unroll
                for (int o = 1; o < 8; o <<= 1) M = fmaxf(M, __shfl_xor_sync(0xffffffffu, M, o));
                const float w = src < CL ? ex2((m - M) * LOG2E) : 0.f;
                float L = w * (src < CL ? st.y : 0.f);
#pragma unroll
                for (int o = 1; o < 8; o <<= 1) L += __shfl_xor_sync(0xffffffffu, L, o);
                if (lane < 16) reinterpret_cast<float*>(sm + S_F)[lane] = w * rcp(L);
            }
            if (j == 9 && tid < 96) {
                if (!pkt_ok(modw, tag)) modw = poll_pkt(modp, tag);
                *reinterpret_cast<float4*>(sm + S_G + tid * 16) = make_float4(bf_hi(modw.x), bf_hi(modw.y), bf_hi(modw.z), bf_hi(modw.w));
            }
            if (j == 13 && wid != 0) mbar_wait_cl(bars + 8 * BAR_DS);
        }
        const float v = (t4 & 2) ? ((t4 & 1) ? c0[3] + c1[3] : c0[2] + c1[2]) : ((t4 & 1) ? c0[1] + c1[1] : c0[0] + c1[0]);
        bcast_word(rb, S_IN + (r * 288 + (t4 & 1) * 128 + wid * 16 + gq + (t4 >> 1) * 8) * 4, __float_as_uint(v), S_BARS + 8 * BAR_DO);
    }
    STAMP(7);
    cbar();
    {
        const float* f = reinterpret_cast<const float*>(sm + S_F) + (tid >> 7) * 8;
        const float f0 = f[0], f1 = f[1], f2 = f[2], f3 = f[3], f4 = f[4], f5 = f[5];
        mbar_wait_cl(bars + 8 * BAR_DO);
        const float* in = inbox + tid;
        const float o = (fmaf(f0, in[0], f1 * in[288]) + fmaf(f2, in[576], f3 * in[864])) + fmaf(f4, in[1152], f5 * in[1440]);
        reinterpret_cast<uint16_t*>(sm + S_QS)[tid] = (uint16_t)pack2(o, 0.f);
    }
    cbar();
    STAMP(8);

    if (wid < 6) {
        uint32_t ob[8][4];
#pragma unroll
        for (int j = 0; j < 8; j++) ld_vec2(ob[j], sb + S_QS, j, mi);
        float c0[4] = {0.f, 0.f, 0.f, 0.f}, c1[4] = {0.f, 0.f, 0.f, 0.f};
        const int rl = (mi >> 1) * 8 + l7;
        const bool pa = wid < 4;
        const uint32_t base = pa ? sb + OFF_WOA + rl * 128 + (((2 * wid + (mi & 1)) ^ l7) << 4)
                                 : sb + OFF_WOB + rl * 64 + (((2 * (wid - 4) + (mi & 1)) ^ ((rl >> 1) & 3)) << 4);
        const uint32_t step = pa ? 16 * 128 : 16 * 64;
#pragma unroll
        for (int q = 0; q < 4; q++) {
            mbar_wait(bars + 8 * (pos_o + (pa ? pos_a(q) : pos_b(q >> 1))));
            uint32_t a[4][4];
#pragma unroll
            for (int i = 0; i < 4; i++) ldsm4t(a[i], base + (4 * q + i) * step);
            mma16816(c0, a[0], ob[2 * q][0], ob[2 * q][1]);
            mma16816(c1, a[1], ob[2 * q][2], ob[2 * q][3]);
            mma16816(c0, a[2], ob[2 * q + 1][0], ob[2 * q + 1][1]);
            mma16816(c1, a[3], ob[2 * q + 1][2], ob[2 * q + 1][3]);
        }
        if (t4 < 2)
            st_word(mail + MB_P1 + b * 96 + cm_w + t4 * 8 + gq, word_f32(t4 ? c0[2] + c1[2] : c0[0] + c1[0], tag));
    }
    STAMP(9);

    if (wid < 6) {
        const float4 ga = *reinterpret_cast<const float4*>(sm + S_G + pc * 16);
        const uint32_t* src = mail + MB_P1 + ((lane >> 2) * CL + r) * 96 + pc * 4;
        if (T_DELAY_G1 > 0) spin_cycles(T_DELAY_G1);
        uint4 u, w;
        if (T_GAP_G1 > 0) poll_pkt2_x2(src, src + 8 * CL * 96, tag, T_GAP_G1, u, w);
        else poll_pkt2(src, src + 8 * CL * 96, tag, u, w);
        float a0 = unword(u.x) + unword(w.x), a1 = unword(u.y) + unword(w.y);
        float a2 = unword(u.z) + unword(w.z), a3 = unword(u.w) + unword(w.w);
#pragma unroll
        for (int o = 4; o < 32; o <<= 1) {
            a0 += __shfl_xor_sync(0xffffffffu, a0, o);
            a1 += __shfl_xor_sync(0xffffffffu, a1, o);
            a2 += __shfl_xor_sync(0xffffffffu, a2, o);
            a3 += __shfl_xor_sync(0xffffffffu, a3, o);
        }
        a0 = rbf(xown.x + rbf(ga.x * rbf(a0))); a1 = rbf(xown.y + rbf(ga.y * rbf(a1)));
        a2 = rbf(xown.z + rbf(ga.z * rbf(a2))); a3 = rbf(xown.w + rbf(ga.w * rbf(a3)));
        if (gq < CL) st_async4(mapa(sb + S_X + (r * 96 + pc * 4) * 4, gq), a0, a1, a2, a3, mapa(bars + 8 * BAR_DX, gq));
    }
    STAMP(10);

    uint32_t w1f[3][6][4];
    {
        const uint32_t wb = bars + 8 * pos_w1;
        mbar_wait2(wb + 16 * (wid >> 2), wb + 16 * (wid >> 2) + 8);
        mbar_wait2(wb + 16 * (2 + (wid >> 2)), wb + 16 * (2 + (wid >> 2)) + 8);
        if (wid < 2) mbar_wait(wb + 64);
#pragma unroll
        for (int s = 0; s < 6; s++) {
            const int row = s * 16 + (mi >> 1) * 8 + l7;
            const uint32_t ra = sb + OFF_W1A + (wid >> 2) * 12288 + row * 128 + (((2 * (wid & 3) + (mi & 1)) ^ l7) << 4);
            ldsm4t(w1f[0][s], ra);
            ldsm4t(w1f[1][s], ra + 2 * 12288);
            if (wid < 2) ldsm4t(w1f[2][s], sb + OFF_W1B + row * 64 + (((2 * wid + (mi & 1)) ^ ((row >> 1) & 3)) << 4));
            else { w1f[2][s][0] = w1f[2][s][1] = w1f[2][s][2] = w1f[2][s][3] = 0u; }
        }
    }

    if (wid == 0) {
        const int j = lane < 24 ? lane : 0;
        const float4 sv2 = *reinterpret_cast<const float4*>(sm + S_G + 768 + j * 16);
        const float4 cb = *reinterpret_cast<const float4*>(sm + S_G + 1152 + j * 16);
        mbar_wait_cl(bars + 8 * BAR_DX);
        STAMP(11);
        const float4 v = *reinterpret_cast<const float4*>(xs + r * 96 + j * 4);
        float mean_b, inv_den;
        ln_stats(xs, lane, mean_b, inv_den);
        const float h0 = rbf(rbf(rbf(v.x - mean_b) * inv_den) * cb.x) + sv2.x;
        const float h1 = rbf(rbf(rbf(v.y - mean_b) * inv_den) * cb.y) + sv2.y;
        const float h2 = rbf(rbf(rbf(v.z - mean_b) * inv_den) * cb.z) + sv2.z;
        const float h3 = rbf(rbf(rbf(v.w - mean_b) * inv_den) * cb.w) + sv2.w;
        if (lane < 24) *reinterpret_cast<uint2*>(sm + S_H + lane * 8) = make_uint2(pack2(h0, h1), pack2(h2, h3));
    }
    cbar();
    STAMP(12);

    {
        uint32_t hb[6][2];
#pragma unroll
        for (int s = 0; s < 6; s++) { hb[s][0] = lds32(sb + S_H + (s * 16 + 2 * t4) * 2); hb[s][1] = lds32(sb + S_H + (s * 16 + 8 + 2 * t4) * 2); }
#pragma unroll
        for (int m = 0; m < 6; m++) { acc[m][0] = acc[m][1] = acc[m][2] = acc[m][3] = 0.f; }
#pragma unroll
        for (int s = 0; s < 6; s++) {
            mma16816(acc[(s & 1) * 3 + 0], w1f[0][s], hb[s][0], hb[s][1]);
            mma16816(acc[(s & 1) * 3 + 1], w1f[1][s], hb[s][0], hb[s][1]);
            if (wid < 2) mma16816(acc[(s & 1) * 3 + 2], w1f[2][s], hb[s][0], hb[s][1]);
        }
        const int ua = (g & 1) * 32, ub = (g & 1) ? 0 : 256;
        const float v = (t4 & 2) ? ((t4 & 1) ? acc[1][2] + acc[4][2] : acc[1][0] + acc[4][0]) : ((t4 & 1) ? acc[0][2] + acc[3][2] : acc[0][0] + acc[3][0]);
        bcast_word(rb, S_IN + (r * 288 + ua + (wid + (t4 >> 1) * 8) * 16 + (t4 & 1) * 8 + gq) * 4, __float_as_uint(v), S_BARS + 8 * BAR_DH);
        if (wid < 2 && t4 < 2)
            bcast_word(rb, S_IN + (r * 288 + ub + wid * 16 + t4 * 8 + gq) * 4,
                       __float_as_uint(t4 ? acc[2][2] + acc[5][2] : acc[2][0] + acc[5][0]), S_BARS + 8 * BAR_DH);
    }
    STAMP(13);

    if (wid >= 6) {
        mbar_wait_cl(bars + 8 * BAR_DH);
#pragma unroll
        for (int i = 0; i < 2; i++) {
            const int u = (tid - 192 + i * 64) * 4;
            if (u < 288) {
                const float* in = inbox + u;
                const float4 a0 = *reinterpret_cast<const float4*>(in), a1 = *reinterpret_cast<const float4*>(in + 288);
                const float4 a2 = *reinterpret_cast<const float4*>(in + 576), a3 = *reinterpret_cast<const float4*>(in + 864);
                const float4 a4 = *reinterpret_cast<const float4*>(in + 1152), a5 = *reinterpret_cast<const float4*>(in + 1440);
                const float t0 = rbf(((a0.x + a1.x) + (a2.x + a3.x)) + (a4.x + a5.x)), t1 = rbf(((a0.y + a1.y) + (a2.y + a3.y)) + (a4.y + a5.y));
                const float t2 = rbf(((a0.z + a1.z) + (a2.z + a3.z)) + (a4.z + a5.z)), t3 = rbf(((a0.w + a1.w) + (a2.w + a3.w)) + (a4.w + a5.w));
                *reinterpret_cast<uint2*>(sm + S_HV + u * 2) =
                    make_uint2(pack2(t0 * rcp(1.0f + ex2(-t0 * LOG2E)), t1 * rcp(1.0f + ex2(-t1 * LOG2E))),
                               pack2(t2 * rcp(1.0f + ex2(-t2 * LOG2E)), t3 * rcp(1.0f + ex2(-t3 * LOG2E))));
            }
        }
        cbar();
    } else {
        uint32_t w2f[18][4];
        const uint32_t wb = bars + 8 * pos_w2;
        const int rl = (mi >> 1) * 8 + l7;
        const bool pa = wid < 4;
        const uint32_t base = pa ? sb + OFF_W2A + rl * 128 + (((2 * wid + (mi & 1)) ^ l7) << 4)
                                 : sb + OFF_W2B + rl * 64 + (((2 * (wid - 4) + (mi & 1)) ^ ((rl >> 1) & 3)) << 4);
        const uint32_t step = pa ? 16 * 128 : 16 * 64;
#pragma unroll
        for (int q = 0; q < 5; q++) {
            mbar_wait(wb + 8 * (pa ? pos_a(q) : pos_b(q >> 1)));
#pragma unroll
            for (int i = 0; i < 3; i++) ldsm4t(w2f[3 * q + i], base + (3 * q + i) * step);
        }
        const uint32_t last = wb + 8 * (pa ? pos_a(5) : pos_b(2));
        const bool pre = mbar_test(last);
        if (pre) {
#pragma unroll
            for (int i = 0; i < 3; i++) ldsm4t(w2f[15 + i], base + (15 + i) * step);
        }
        cbar();
        STAMP(21);
        uint32_t vb[9][4];
#pragma unroll
        for (int j = 0; j < 9; j++) ld_vec2(vb[j], sb + S_HV, j, mi);
        float c[3][4];
#pragma unroll
        for (int i = 0; i < 3; i++) { c[i][0] = c[i][1] = c[i][2] = c[i][3] = 0.f; }
#pragma unroll
        for (int s = 0; s < 15; s++) mma16816(c[s % 3], w2f[s], vb[s >> 1][2 * (s & 1)], vb[s >> 1][2 * (s & 1) + 1]);
        if (!pre) {
            mbar_wait(last);
#pragma unroll
            for (int i = 0; i < 3; i++) ldsm4t(w2f[15 + i], base + (15 + i) * step);
        }
#pragma unroll
        for (int s = 15; s < 18; s++) mma16816(c[s % 3], w2f[s], vb[s >> 1][2 * (s & 1)], vb[s >> 1][2 * (s & 1) + 1]);
        if (t4 < 2)
            st_word(mail + MB_P2 + b * 96 + cm_w + t4 * 8 + gq,
                    word_f32(t4 ? (c[0][2] + c[1][2]) + c[2][2] : (c[0][0] + c[1][0]) + c[2][0], tag));
    }
    STAMP(14);

    if (g < 12 && wid == 0) {
        const int col = g * 8 + (lane & 1) * 4;
        const float4 gb = *reinterpret_cast<const float4*>(sm + S_G + 384 + col * 4);
        const float4 x2 = *reinterpret_cast<const float4*>(xs + r * 96 + col);
        if (T_DELAY_G2 > 0) spin_cycles(T_DELAY_G2);
        const uint32_t* src = mail + MB_P2 + ((lane >> 1) * CL + r) * 96 + col;
        const uint4 u = T_GAP_G2 > 0 ? poll_pkt_x2(src, tag, T_GAP_G2) : poll_pkt(src, tag);
        float a0 = unword(u.x), a1 = unword(u.y), a2 = unword(u.z), a3 = unword(u.w);
#pragma unroll
        for (int o = 2; o < 32; o <<= 1) {
            a0 += __shfl_xor_sync(0xffffffffu, a0, o);
            a1 += __shfl_xor_sync(0xffffffffu, a1, o);
            a2 += __shfl_xor_sync(0xffffffffu, a2, o);
            a3 += __shfl_xor_sync(0xffffffffu, a3, o);
        }
        if (lane < 2) {
            const uint2 o = make_uint2(pack2(x2.x + rbf(gb.x * rbf(a0)), x2.y + rbf(gb.y * rbf(a1))),
                                       pack2(x2.z + rbf(gb.z * rbf(a2)), x2.w + rbf(gb.w * rbf(a3))));
            *reinterpret_cast<uint2*>(p.out + r * 96 + col) = o;
        }
        if (b == 0 && lane == 0) g_count = (cnt >= 2u) ? 0u : cnt + 1u;
    }
    STAMP(15);
}

typedef CUresult (*EncodeTiledFn)(CUtensorMap*, CUtensorMapDataType, cuuint32_t, void*, const cuuint64_t*, const cuuint64_t*,
                                  const cuuint32_t*, const cuuint32_t*, CUtensorMapInterleave, CUtensorMapSwizzle,
                                  CUtensorMapL2promotion, CUtensorMapFloatOOBfill);

void encode2d(EncodeTiledFn enc, CUtensorMap* m, const void* ptr, uint64_t cols, uint64_t rows, uint32_t bc, uint32_t br,
              CUtensorMapSwizzle sw) {
    cuuint64_t dims[2] = {cols, rows};
    cuuint64_t str[1] = {cols * 2};
    cuuint32_t box[2] = {bc, br};
    cuuint32_t es[2] = {1, 1};
    enc(m, CU_TENSOR_MAP_DATA_TYPE_BFLOAT16, 2, const_cast<void*>(ptr), dims, str, box, es, CU_TENSOR_MAP_INTERLEAVE_NONE, sw,
        CU_TENSOR_MAP_L2_PROMOTION_L2_128B, CU_TENSOR_MAP_FLOAT_OOB_FILL_NONE);
}
void encode_kv(EncodeTiledFn enc, CUtensorMap* m, const void* ptr) {
    cuuint64_t dims[3] = {64, 16ull * SK_, 2};
    cuuint64_t str[2] = {256, 128};
    cuuint32_t box[3] = {64, 32, 2};
    cuuint32_t es[3] = {1, 1, 1};
    enc(m, CU_TENSOR_MAP_DATA_TYPE_BFLOAT16, 3, const_cast<void*>(ptr), dims, str, box, es, CU_TENSOR_MAP_INTERLEAVE_NONE,
        CU_TENSOR_MAP_SWIZZLE_128B, CU_TENSOR_MAP_L2_PROMOTION_L2_128B, CU_TENSOR_MAP_FLOAT_OOB_FILL_NONE);
}

}

extern "C" void kernel_launch(void* const* d_in, const int* in_sizes, int n_in, void* d_out, int out_size) {
    (void)in_sizes; (void)n_in; (void)out_size;
    static EncodeTiledFn enc = nullptr;
    if (!enc) {
        void* fn = nullptr;
        cudaDriverEntryPointQueryResult qr;
        cudaGetDriverEntryPoint("cuTensorMapEncodeTiled", &fn, cudaEnableDefault, &qr);
        enc = (EncodeTiledFn)fn;
        cudaFuncSetAttribute(adaln_attn_mlp_decode_kernel, cudaFuncAttributeMaxDynamicSharedMemorySize, SMEM_BYTES);
    }
    Maps maps;
    encode2d(enc, &maps.wmod, d_in[9], 3456, 576, 40, 96, CU_TENSOR_MAP_SWIZZLE_NONE);
    encode2d(enc, &maps.wq, d_in[3], 4096, 576, 64, 48, CU_TENSOR_MAP_SWIZZLE_128B);
    encode_kv(enc, &maps.k, d_in[1]);
    encode_kv(enc, &maps.v, d_in[2]);
    encode2d(enc, &maps.woa, d_in[4], 576, 4096, 64, 64, CU_TENSOR_MAP_SWIZZLE_128B);
    encode2d(enc, &maps.wob, d_in[4], 576, 4096, 32, 128, CU_TENSOR_MAP_SWIZZLE_64B);
    encode2d(enc, &maps.w1a, d_in[6], F_, 576, 64, 48, CU_TENSOR_MAP_SWIZZLE_128B);
    encode2d(enc, &maps.w1b, d_in[6], F_, 576, 32, 96, CU_TENSOR_MAP_SWIZZLE_64B);
    encode2d(enc, &maps.w2a, d_in[7], 576, F_, 64, 48, CU_TENSOR_MAP_SWIZZLE_128B);
    encode2d(enc, &maps.w2b, d_in[7], 576, F_, 32, 96, CU_TENSOR_MAP_SWIZZLE_64B);
    Ptrs p;
    p.x = (const __nv_bfloat16*)d_in[0];
    p.c = (const __nv_bfloat16*)d_in[8];
    p.out = (__nv_bfloat16*)d_out;
    cudaLaunchConfig_t cfg = {};
    cfg.gridDim = dim3(NCTA);
    cfg.blockDim = dim3(NTHREADS);
    cfg.dynamicSmemBytes = SMEM_BYTES;
    cfg.stream = cudaStreamPerThread;
    cudaLaunchAttribute at[1];
    at[0].id = cudaLaunchAttributeClusterDimension;
    at[0].val.clusterDim.x = CL; at[0].val.clusterDim.y = 1; at[0].val.clusterDim.z = 1;
    cfg.attrs = at;
    cfg.numAttrs = 1;
    cudaLaunchKernelEx(&cfg, adaln_attn_mlp_decode_kernel, maps, p);
}
```

```cpp
#include <cuda_runtime.h>
#include <cuda_bf16.h>
#include <cuda.h>
#include <stdint.h>

namespace {

constexpr int SK_ = 65536, WIN_ = 4096, F_ = 4608;
constexpr int CL = 6, NCL = 16, NCTA = CL * NCL, NTHREADS = 288;
constexpr int NP1 = 32;

constexpr int P_KV = 14, N_ITEMS = 14 + 44 + 6 + 9 + 9;
constexpr int BAR_CK = N_ITEMS;
constexpr int BAR_CV = BAR_CK + 22;
constexpr int BAR_DQ = BAR_CV + 22;
constexpr int BAR_DS = BAR_DQ + 1, BAR_DO = BAR_DQ + 2, BAR_DX = BAR_DQ + 3, BAR_DH = BAR_DQ + 4;
constexpr int N_BARS = BAR_DQ + 5;
__host__ __device__ constexpr int pos_a(int j) { return j + (j + 1) / 2; }
__host__ __device__ constexpr int pos_b(int j) { return 1 + 3 * j; }

constexpr int OFF_WOA = 0;
constexpr int OFF_WOB = 32768;
constexpr int OFF_W1A = 49152;
constexpr int OFF_W1B = OFF_W1A + 49152;
constexpr int OFF_W2A = OFF_W1B + 6144;
constexpr int OFF_W2B = OFF_W2A + 36864;
constexpr int OFF_M = 0;
constexpr int OFF_Q = 46080;
constexpr int OFF_X = 95232;
constexpr int OFF_SMALL = OFF_X + 14 * 8192;
constexpr int S_BARS = OFF_SMALL;
constexpr int S_H = S_BARS + 1088;
constexpr int S_X = S_H + 192;
constexpr int S_IN = S_X + 2304;
constexpr int S_QS = S_IN + 6912;
constexpr int S_P = S_QS + 512;
constexpr int S_PART = S_P + 2848;
constexpr int S_RED = S_PART + 3072;
constexpr int S_ST = S_RED + 256;
constexpr int S_F = S_ST + 96;
constexpr int S_HV = S_F + 64;
constexpr int S_G = S_HV + 576;
constexpr int S_MISC = S_G + 1536;
constexpr int S_DESC = S_MISC + 32;
constexpr int SMEM_BYTES = S_DESC + 384;
static_assert(N_BARS * 8 <= 1088, "barriers");
static_assert(OFF_W2B + 18432 <= OFF_X + 8 * 8192, "late weights");
static_assert(SMEM_BYTES <= 232448, "smem");
constexpr int PROW = 712;

#define RATE_KV 3240.0f
#define RATE_LATE 3300.0f
#define WIN_KV 8
#define WIN_LATE 8
#define WIN_L6 8
#define NFIRST 4
#define LATE_FROM 18
#define P1_Q_STEP 150.0f
#define DELAY_G1 600
#define LAT_G1 1900
#define LAT_G2 0
#define GAP_G1 0
#define GAP_G2 300
#define DELAY_G2 150
constexpr float BYTES_22 = 46080.f + 49152.f + 44 * 8192.f + 49152.f + 55296.f + 55296.f;
constexpr float BYTES_21 = BYTES_22 - 2 * 8192.f;
constexpr float BYTES_ALL = 2 * NCL * BYTES_22 + 4 * NCL * BYTES_21;

#define T_RATE_KV RATE_KV
#define T_RATE_LATE RATE_LATE
#define T_WIN_KV WIN_KV
#define T_WIN_LATE WIN_LATE
#define T_LATE_FROM LATE_FROM
#define T_WIN_L6 WIN_L6
#define T_GAP_G1 GAP_G1
#define T_LAT_G1 LAT_G1
#define T_LAT_G2 LAT_G2
#define T_GAP_G2 GAP_G2
#define T_P1_Q_STEP P1_Q_STEP
#define T_DELAY_G1 DELAY_G1
#define T_DELAY_G2 DELAY_G2

struct Maps { CUtensorMap wmod, wq, k, v, woa, wob, w1a, w1b, w2a, w2b; };
struct Ptrs {
    const __nv_bfloat16 *x, *c;
    __nv_bfloat16* out;
};

constexpr int MB_MOD = 0;
constexpr int MB_P1 = MB_MOD + NCTA * 40;
constexpr int MB_P2 = MB_P1 + NCTA * 96;
constexpr int MB_END = MB_P2 + NCTA * 96;
__device__ __align__(128) uint32_t g_mail[MB_END];
__device__ uint32_t g_count;

__device__ __forceinline__ uint32_t smem_u32(const void* p) { return (uint32_t)__cvta_generic_to_shared(p); }
__device__ __forceinline__ void mbar_init(uint32_t bar, uint32_t cnt) {
    asm volatile("mbarrier.init.shared::cta.b64 [%0], %1;" ::"r"(bar), "r"(cnt));
}
__device__ __forceinline__ void mbar_expect_tx(uint32_t bar, uint32_t bytes) {
    asm volatile("mbarrier.arrive.expect_tx.shared::cta.b64 _, [%0], %1;" ::"r"(bar), "r"(bytes) : "memory");
}
__device__ __forceinline__ void mbar_arrive(uint32_t bar) {
    asm volatile("mbarrier.arrive.shared::cta.b64 _, [%0];" ::"r"(bar) : "memory");
}
constexpr int SPIN_LIMIT = 1 << 18;
__device__ __forceinline__ uint32_t mbar_try(uint32_t bar) {
    uint32_t ok;
    asm volatile("{\n.reg .pred p;\nmbarrier.try_wait.parity.shared::cta.b64 p, [%1], 0;\nselp.u32 %0, 1, 0, p;\n}"
                 : "=r"(ok) : "r"(bar) : "memory");
    return ok;
}
__device__ __forceinline__ uint32_t mbar_test(uint32_t bar) {
    uint32_t ok;
    asm volatile("{\n.reg .pred p;\nmbarrier.test_wait.parity.shared::cta.b64 p, [%1], 0;\nselp.u32 %0, 1, 0, p;\n}"
                 : "=r"(ok) : "r"(bar) : "memory");
    return ok;
}
__device__ __forceinline__ void mbar_wait(uint32_t bar) {
    int it = 0;
    while (!mbar_try(bar) && ++it < SPIN_LIMIT) {}
}
__device__ __forceinline__ void mbar_wait2(uint32_t bar0, uint32_t bar1) {
    int it = 0;
    while (!(mbar_try(bar0) & mbar_try(bar1)) && ++it < SPIN_LIMIT) {}
}
__device__ __forceinline__ void mbar_wait_cl(uint32_t bar) {
    uint32_t ok;
    int it = 0;
    do {
        asm volatile("{\n.reg .pred p;\nmbarrier.try_wait.parity.acquire.cluster.shared::cta.b64 p, [%1], 0;\nselp.u32 %0, 1, 0, p;\n}"
                     : "=r"(ok) : "r"(bar) : "memory");
    } while (!ok && ++it < SPIN_LIMIT);
}
__device__ __forceinline__ uint32_t mapa(uint32_t a, uint32_t rank) {
    uint32_t d;
    asm("mapa.shared::cluster.u32 %0, %1, %2;" : "=r"(d) : "r"(a), "r"(rank));
    return d;
}
__device__ __forceinline__ void st_async1(uint32_t dst, uint32_t v, uint32_t bar) {
    asm volatile("st.async.weak.shared::cluster.mbarrier::complete_tx::bytes.b32 [%0], %1, [%2];" ::"r"(dst), "r"(v), "r"(bar) : "memory");
}
__device__ __forceinline__ void st_async4(uint32_t dst, float a, float b, float c, float d, uint32_t bar) {
    asm volatile("st.async.weak.shared::cluster.mbarrier::complete_tx::bytes.v4.f32 [%0], {%1, %2, %3, %4}, [%5];"
                 ::"r"(dst), "f"(a), "f"(b), "f"(c), "f"(d), "r"(bar) : "memory");
}
__device__ __forceinline__ void bcast_word(const uint32_t (&rb)[CL], uint32_t off, uint32_t v, uint32_t bar_off) {
#pragma unroll
    for (int d = 0; d < CL; d++) st_async1(rb[d] + off, v, rb[d] + bar_off);
}
__device__ __forceinline__ void tma2d(uint32_t dst, const CUtensorMap* m, int c0, int c1, uint32_t bar) {
    asm volatile("cp.async.bulk.tensor.2d.shared::cluster.global.mbarrier::complete_tx::bytes [%0], [%1, {%3, %4}], [%2];"
                 ::"r"(dst), "l"(m), "r"(bar), "r"(c0), "r"(c1) : "memory");
}
__device__ __forceinline__ void tma3d(uint32_t dst, const CUtensorMap* m, int c0, int c1, int c2, uint32_t bar, uint64_t pol) {
    asm volatile("cp.async.bulk.tensor.3d.shared::cluster.global.mbarrier::complete_tx::bytes.L2::cache_hint [%0], [%1, {%3, %4, %5}], [%2], %6;"
                 ::"r"(dst), "l"(m), "r"(bar), "r"(c0), "r"(c1), "r"(c2), "l"(pol) : "memory");
}
__device__ __forceinline__ void issue2d(uint32_t bar, uint32_t bytes, uint32_t dst, const CUtensorMap* m, int c0, int c1) {
    asm volatile("{\n.reg .pred p;\nelect.sync _|p, 0xffffffff;\n"
                 "@p mbarrier.arrive.expect_tx.shared::cta.b64 _, [%0], %1;\n"
                 "@p cp.async.bulk.tensor.2d.shared::cluster.global.mbarrier::complete_tx::bytes [%2], [%3, {%4, %5}], [%0];\n}"
                 ::"r"(bar), "r"(bytes), "r"(dst), "l"(m), "r"(c0), "r"(c1) : "memory");
}
__device__ __forceinline__ void issue3d(uint32_t bar, uint32_t dst, const CUtensorMap* m, int row, uint64_t pol) {
    asm volatile("{\n.reg .pred p;\nelect.sync _|p, 0xffffffff;\n"
                 "@p mbarrier.arrive.expect_tx.shared::cta.b64 _, [%0], 8192;\n"
                 "@p cp.async.bulk.tensor.3d.shared::cluster.global.mbarrier::complete_tx::bytes.L2::cache_hint [%1], [%2, {0, %3, 0}], [%0], %4;\n}"
                 ::"r"(bar), "r"(dst), "l"(m), "r"(row), "l"(pol) : "memory");
}
__device__ __forceinline__ void ldsm4(uint32_t (&r)[4], uint32_t a) {
    asm volatile("ldmatrix.sync.aligned.m8n8.x4.shared.b16 {%0, %1, %2, %3}, [%4];"
                 : "=r"(r[0]), "=r"(r[1]), "=r"(r[2]), "=r"(r[3]) : "r"(a) : "memory");
}
__device__ __forceinline__ void ldsm4t(uint32_t (&r)[4], uint32_t a) {
    asm volatile("ldmatrix.sync.aligned.m8n8.x4.trans.shared.b16 {%0, %1, %2, %3}, [%4];"
                 : "=r"(r[0]), "=r"(r[1]), "=r"(r[2]), "=r"(r[3]) : "r"(a) : "memory");
}
__device__ __forceinline__ void mma16816(float (&c)[4], const uint32_t (&a)[4], uint32_t b0, uint32_t b1) {
    asm volatile("mma.sync.aligned.m16n8k16.row.col.f32.bf16.bf16.f32 {%0, %1, %2, %3}, {%4, %5, %6, %7}, {%8, %9}, {%0, %1, %2, %3};"
                 : "+f"(c[0]), "+f"(c[1]), "+f"(c[2]), "+f"(c[3])
                 : "r"(a[0]), "r"(a[1]), "r"(a[2]), "r"(a[3]), "r"(b0), "r"(b1));
}
__device__ __forceinline__ uint32_t lds32(uint32_t a) {
    uint32_t v;
    asm volatile("ld.shared.b32 %0, [%1];" : "=r"(v) : "r"(a) : "memory");
    return v;
}
__device__ __forceinline__ void cbar() { asm volatile("bar.sync 1, 256;" ::: "memory"); }

__device__ __forceinline__ void st_word(uint32_t* p, uint32_t v) {
    asm volatile("st.relaxed.gpu.global.b32 [%0], %1;" ::"l"(p), "r"(v) : "memory");
}
__device__ __forceinline__ uint4 ld_pkt(const uint32_t* p) {
    uint4 v;
    asm volatile("ld.relaxed.gpu.global.v4.b32 {%0, %1, %2, %3}, [%4];"
                 : "=r"(v.x), "=r"(v.y), "=r"(v.z), "=r"(v.w) : "l"(p) : "memory");
    return v;
}
__device__ __forceinline__ bool pkt_ok(const uint4& v, uint32_t tag) {
    return (((v.x ^ tag) | (v.y ^ tag) | (v.z ^ tag) | (v.w ^ tag)) & 3u) == 0u;
}
__device__ __forceinline__ void spin_cycles(uint32_t n) {
    uint32_t c0, c1;
    asm volatile("mov.u32 %0, %%clock;" : "=r"(c0));
    do { asm volatile("mov.u32 %0, %%clock;" : "=r"(c1)); } while (c1 - c0 < n);
}
__device__ __forceinline__ uint4 poll_pkt(const uint32_t* p, uint32_t tag) {
    uint4 v;
    int it = 0;
    do { v = ld_pkt(p); } while (!pkt_ok(v, tag) && ++it < SPIN_LIMIT);
    return v;
}
__device__ __forceinline__ void poll_pkt2(const uint32_t* p, const uint32_t* q, uint32_t tag, uint4& v, uint4& w) {
    int it = 0;
    do { v = ld_pkt(p); w = ld_pkt(q); } while (!(pkt_ok(v, tag) && pkt_ok(w, tag)) && ++it < SPIN_LIMIT);
}
__device__ __forceinline__ uint4 poll_pkt_x2(const uint32_t* p, uint32_t tag, uint32_t gap) {
    uint4 a = ld_pkt(p);
    spin_cycles(gap);
    uint4 c = ld_pkt(p);
    for (int it = 0; it < SPIN_LIMIT; it++) {
        if (pkt_ok(a, tag)) return a;
        a = ld_pkt(p);
        if (pkt_ok(c, tag)) return c;
        c = ld_pkt(p);
    }
    return a;
}
__device__ __forceinline__ void poll_pkt2_x2(const uint32_t* p, const uint32_t* q, uint32_t tag, uint32_t gap, uint4& v, uint4& w) {
    uint4 a0 = ld_pkt(p), a1 = ld_pkt(q);
    spin_cycles(gap);
    uint4 c0 = ld_pkt(p), c1 = ld_pkt(q);
    for (int it = 0; it < SPIN_LIMIT; it++) {
        if (pkt_ok(a0, tag) && pkt_ok(a1, tag)) { v = a0; w = a1; return; }
        a0 = ld_pkt(p); a1 = ld_pkt(q);
        if (pkt_ok(c0, tag) && pkt_ok(c1, tag)) { v = c0; w = c1; return; }
        c0 = ld_pkt(p); c1 = ld_pkt(q);
    }
    v = a0; w = a1;
}
__device__ __forceinline__ uint32_t pack2(float lo, float hi) {
    uint32_t u;
    asm("cvt.rn.bf16x2.f32 %0, %1, %2;" : "=r"(u) : "f"(hi), "f"(lo));
    return u;
}
__device__ __forceinline__ float rbf(float x) { return __uint_as_float(pack2(0.f, x)); }
__device__ __forceinline__ float ex2(float x) { float y; asm("ex2.approx.ftz.f32 %0, %1;" : "=f"(y) : "f"(x)); return y; }
__device__ __forceinline__ float rcp(float x) { float y; asm("rcp.approx.ftz.f32 %0, %1;" : "=f"(y) : "f"(x)); return y; }
__device__ __forceinline__ float sqrt_a(float x) { float y; asm("sqrt.approx.ftz.f32 %0, %1;" : "=f"(y) : "f"(x)); return y; }
constexpr float LOG2E = 1.4426950408889634f;
__device__ __forceinline__ uint32_t word_bf(float x_rounded, uint32_t tag) { return __float_as_uint(x_rounded) | tag; }
__device__ __forceinline__ uint32_t word_f32(float x, uint32_t tag) { return (__float_as_uint(x) & ~3u) | tag; }
__device__ __forceinline__ float unword(uint32_t w) { return __uint_as_float(w & ~3u); }
__device__ __forceinline__ float bf_lo(uint32_t w) { return __uint_as_float(w << 16); }
__device__ __forceinline__ float bf_hi(uint32_t w) { return __uint_as_float(w & 0xFFFF0000u); }
__device__ __forceinline__ uint32_t pack_hi(uint32_t a, uint32_t b) { return __byte_perm(a, b, 0x7632); }
__device__ __forceinline__ uint32_t gtime() { unsigned long long t; asm volatile("mov.u64 %0, %%globaltimer;" : "=l"(t)); return (uint32_t)t; }
__device__ __forceinline__ int mod_word(int c) { const int pb = c / 36; return MB_MOD + pb * 40 + (c - pb * 36); }

template <int LO, int HI>
__device__ __forceinline__ void init_bars(uint32_t bars) {
#pragma unroll
    for (int i = LO; i < HI; i++) mbar_init(bars + 8 * i, (i >= BAR_CV && i < BAR_DQ) ? 8 : 1);
}

#define STAMP(i)
#define PSTAMP(i)

__device__ __forceinline__ void ln_stats(const float* xs, int lane, float& mean_b, float& inv_den) {
    float v[18];
    const float c = xs[0];
#pragma unroll
    for (int i = 0; i < 4; i++) {
        const float4 a = *reinterpret_cast<const float4*>(xs + i * 128 + lane * 4);
        v[4 * i] = a.x; v[4 * i + 1] = a.y; v[4 * i + 2] = a.z; v[4 * i + 3] = a.w;
    }
    {
        const float2 a = *reinterpret_cast<const float2*>(xs + 512 + lane * 2);
        v[16] = a.x; v[17] = a.y;
    }
    float s0 = 0.f, s1 = 0.f, s2 = 0.f, q0 = 0.f, q1 = 0.f, q2 = 0.f;
#pragma unroll
    for (int i = 0; i < 18; i += 3) {
        const float d0 = v[i] - c, d1 = v[i + 1] - c, d2 = v[i + 2] - c;
        s0 += d0; s1 += d1; s2 += d2;
        q0 = fmaf(d0, d0, q0); q1 = fmaf(d1, d1, q1); q2 = fmaf(d2, d2, q2);
    }
    float s = (s0 + s1) + s2, q = (q0 + q1) + q2;
#pragma unroll
    for (int o = 16; o > 0; o >>= 1) {
        s += __shfl_xor_sync(0xffffffffu, s, o);
        q += __shfl_xor_sync(0xffffffffu, q, o);
    }
    const float md = s * (1.0f / 576.0f);
    const float var = fmaxf(fmaf(-md, md, q * (1.0f / 576.0f)), 0.f);
    mean_b = rbf(c + md);
    inv_den = rcp(rbf(sqrt_a(rbf(rbf(var) + 1e-5f))));
}

__device__ __forceinline__ void ld_vec2(uint32_t (&b)[4], uint32_t v, int j, int mi) { ldsm4(b, v + (4 * j + mi) * 16); }

__device__ __forceinline__ void ld_ntile(uint32_t (&a)[6][4], uint32_t base_a, uint32_t base_b, int row0, int mi, int l7) {
    const int row = row0 + (mi >> 1) * 8 + l7;
    const uint32_t ra = base_a + row * 128, rb = base_b + row * 64;
#pragma unroll
    for (int m = 0; m < 4; m++) ldsm4t(a[m], ra + (((2 * m + (mi & 1)) ^ l7) << 4));
#pragma unroll
    for (int m = 0; m < 2; m++) ldsm4t(a[4 + m], rb + (((2 * m + (mi & 1)) ^ ((row >> 1) & 3)) << 4));
}

__global__ void __launch_bounds__(NTHREADS, 1)
adaln_attn_mlp_decode_kernel(const __grid_constant__ Maps maps, const Ptrs p) {
    extern __shared__ __align__(1024) uint8_t sm[];
    const uint32_t sb = smem_u32(sm);
    int tid, b, r;
    asm volatile("mov.u32 %0, %%tid.x;" : "=r"(tid));
    asm volatile("mov.u32 %0, %%ctaid.x;" : "=r"(b));
    asm volatile("mov.u32 %0, %%cluster_ctarank;" : "=r"(r));
    const int g = b / CL;
    const int nt = 21 + (r < 2);
    const uint32_t bars = sb + S_BARS;
    const int pos_m = b < NP1 ? 0 : 8, pos_q = b < NP1 ? 6 : 0;
    const int pos_o = P_KV + 2 * nt, pos_w1 = pos_o + 6, pos_w2 = pos_w1 + 9;

    uint32_t t0 = 0;
    if (tid == 256) {
        t0 = gtime();
        PSTAMP(16);
        if (sb & 1023u) __trap();
        init_bars<0, P_KV>(bars);
        asm volatile("fence.proxy.async.shared::cta;" ::: "memory");
        if (b < NP1) {
#pragma unroll
            for (int i = 0; i < 6; i++) {
                mbar_expect_tx(bars + 8 * i, 7680);
                tma2d(sb + OFF_M + i * 7680, &maps.wmod, b * 36 - (b & 1) * 4, i * 96, bars + 8 * i);
            }
        } else {
#pragma unroll
            for (int i = 0; i < NFIRST; i++) {
                mbar_expect_tx(bars + 8 * i, 6144);
                tma2d(sb + OFF_Q + i * 6144, &maps.wq, g * 256 + (i >> 1) * 64, r * 96 + (i & 1) * 48, bars + 8 * i);
            }
        }
    }

    if (tid >= 256) {
        if (tid > 256 && tid <= 256 + 24) {
            const int i = tid - 257;
            const int ca = r * 96 + (r & 1) * 32, cb = r * 96 + ((r & 1) ? 0 : 64);
            const int c1a = g * 288 + (g & 1) * 32, c1b = g * 288 + ((g & 1) ? 0 : 256);
            uint32_t dst, map; int c0, c1;
            if (i < 6) {
                const bool isb = (i == 1 || i == 4);
                const int j = isb ? (i >> 2) : (i == 0 ? 0 : (i == 5 ? 3 : i - 1));
                dst = isb ? OFF_WOB + j * 8192 : OFF_WOA + j * 8192; map = isb ? 5 : 4;
                c0 = isb ? cb : ca; c1 = g * 256 + j * (isb ? 128 : 64);
            } else if (i < 15) {
                const int j = i - 6;
                dst = j < 8 ? OFF_W1A + j * 6144 : OFF_W1B; map = j < 8 ? 6 : 7;
                c0 = j < 8 ? c1a + (j >> 1) * 64 : c1b; c1 = r * 96 + (j < 8 ? (j & 1) * 48 : 0);
            } else {
                const int k = i - 15, q = k / 3, m = k - 3 * q;
                const bool isb = m == 1;
                const int j = isb ? q : 2 * q + (m == 2);
                dst = isb ? OFF_W2B + j * 6144 : OFF_W2A + j * 6144; map = isb ? 9 : 8;
                c0 = isb ? cb : ca; c1 = g * 288 + j * (isb ? 96 : 48);
            }
            *reinterpret_cast<uint4*>(sm + S_DESC + i * 16) = make_uint4(sb + dst, map * 128u, (uint32_t)c0, (uint32_t)c1);
        }
        const float nsb_kv = (r < 2 ? BYTES_ALL / BYTES_22 : BYTES_ALL / BYTES_21) * __frcp_rn(T_RATE_KV);
        const float nsb_late = (r < 2 ? BYTES_ALL / BYTES_22 : BYTES_ALL / BYTES_21) * __frcp_rn(T_RATE_LATE);
        t0 = __shfl_sync(0xffffffffu, t0, 0);
        if (tid == 256) {
            const float t_wo = (46080.f + 49152.f + 8192.f * (nt + T_LATE_FROM)) * nsb_kv + 8192.f * (nt - T_LATE_FROM + 5) * nsb_late;
            reinterpret_cast<uint32_t*>(sm + S_MISC)[1] = t0 + (uint32_t)t_wo + T_LAT_G1;
            reinterpret_cast<uint32_t*>(sm + S_MISC)[2] = t0 + (uint32_t)(t_wo + (8192.f + 17 * 6144.f) * nsb_late) + T_LAT_G2;
        }
        __syncwarp();
        asm volatile("bar.arrive 2, 288;" ::: "memory");
        asm volatile("barrier.cluster.arrive.relaxed.aligned;" ::: "memory");
        uint64_t pol;
        asm volatile("createpolicy.fractional.L2::evict_first.b64 %0, 1.0;" : "=l"(pol));
        uint32_t tn = 0;
        uint32_t bar = bars;
        auto gate = [&](uint32_t wbar, uint32_t t) {
            uint32_t now = gtime();
            mbar_wait(wbar);
            for (int it = 0; now - t0 < t && it < SPIN_LIMIT; it++) now = gtime();
        };
        auto gate2 = [&](uint32_t wbar, uint32_t dep, uint32_t t) {
            uint32_t now = gtime();
            mbar_wait2(wbar, dep);
            for (int it = 0; now - t0 < t && it < SPIN_LIMIT; it++) now = gtime();
        };
#define ITEMLOG()
        {
            const uint32_t st_m = (uint32_t)(7680.f * nsb_kv), st_q = (uint32_t)(6144.f * nsb_kv);
            const int q0 = b < NP1 ? 0 : NFIRST;
            bar += 8 * (b < NP1 ? 6 : NFIRST);
            tn += b < NP1 ? 6 * st_m : NFIRST * st_q;
#pragma unroll 1
            for (int i = q0; i < 8; i++) {
                const uint32_t wb = bar >= bars + 8 * T_WIN_KV ? bar - 8 * T_WIN_KV : bar;
                const uint32_t t = b < NP1 ? (uint32_t)T_P1_Q_STEP * (i + 1) : tn;
                if (wb != bar) gate(wb, t); else for (int it = 0; gtime() - t0 < t && it < SPIN_LIMIT; it++) {}
                ITEMLOG();
                issue2d(bar, 6144, sb + OFF_Q + i * 6144, &maps.wq, g * 256 + (i >> 1) * 64, r * 96 + (i & 1) * 48);
                bar += 8; tn += st_q;
            }
            if (b >= NP1) {
#pragma unroll 1
                for (int i = 0; i < 6; i++) {
                    gate(bar >= bars + 8 * T_WIN_KV ? bar - 8 * T_WIN_KV : bars, tn);
                    ITEMLOG();
                    issue2d(bar, 7680, sb + OFF_M + i * 7680, &maps.wmod, b * 36 - (b & 1) * 4, i * 96);
                    bar += 8; tn += st_m;
                }
            }
        }
        asm volatile("bar.sync 3, 288;" ::: "memory");
        {
            const uint32_t st_kv = (uint32_t)(8192.f * nsb_kv), st_late8 = (uint32_t)(8192.f * nsb_late), st_late6 = (uint32_t)(6144.f * nsb_late);
            const int row0 = g * SK_ + (SK_ - WIN_) + (21 * r + (r < 2 ? r : 2)) * 32;
            uint32_t dst = sb + OFF_X + 12 * 8192;
            int row = row0;
#pragma unroll 1
            for (int i = 0; i < 14; i++) {
                gate(bar - 8 * T_WIN_KV, tn);
                ITEMLOG();
                issue3d(bar, dst, &maps.k, row, pol);
                bar += 8; tn += st_kv; row += 32;
                dst += 8192; if (dst == sb + OFF_X + 14 * 8192) dst = sb + OFF_X;
            }
            uint32_t cons = bars + 8 * BAR_CK;
#pragma unroll 1
            for (int i = 14; i < nt; i++) {
                gate2(bar - 8 * T_WIN_KV, cons, tn);
                ITEMLOG();
                issue3d(bar, dst, &maps.k, row, pol);
                bar += 8; cons += 8; tn += st_kv; row += 32;
                dst += 8192; if (dst == sb + OFF_X + 14 * 8192) dst = sb + OFF_X;
            }
            if (tid == 256) PSTAMP(17);
            row = row0;
#pragma unroll 1
            for (int i = 0; i < nt; i++) {
                const bool late = i >= T_LATE_FROM;
                if (i == 14) cons = bars + 8 * BAR_CV;
                gate2(bar - 8 * (late ? T_WIN_LATE : T_WIN_KV), cons, tn);
                ITEMLOG();
                issue3d(bar, dst, &maps.v, row, pol);
                bar += 8; cons += 8; tn += late ? st_late8 : st_kv; row += 32;
                dst += 8192; if (dst == sb + OFF_X + 14 * 8192) dst = sb + OFF_X;
            }
            if (tid == 256) PSTAMP(18);
            const uint32_t cv = bars + 8 * (BAR_CV + 30 - nt);
            const uint8_t* const mbase = reinterpret_cast<const uint8_t*>(&maps);
#pragma unroll 1
            for (int i = 0; i < 24; i++) {
                const uint4 d = *reinterpret_cast<const uint4*>(sm + S_DESC + i * 16);
                if (i == 13) mbar_wait2(cv, cv + 8);
                if (i == 15) { mbar_wait2(cv + 16, cv + 24); mbar_wait2(cv + 32, cv + 40); mbar_wait2(cv + 48, cv + 56); }
                gate(bar - 8 * (i < 6 ? T_WIN_LATE : T_WIN_L6), tn);
                ITEMLOG();
                issue2d(bar, i < 6 ? 8192 : 6144, d.x, reinterpret_cast<const CUtensorMap*>(mbase + d.y), (int)d.z, (int)d.w);
                bar += 8; tn += i < 6 ? st_late8 : st_late6;
            }
            if (tid == 256) PSTAMP(19);
        }
        return;
    }

    const int lane = tid & 31, wid = tid >> 5;
    const int gq = lane >> 2, t4 = lane & 3;
    const int mi = lane >> 3, l7 = lane & 7;
    float* const xs = reinterpret_cast<float*>(sm + S_X);
    float* const part = reinterpret_cast<float*>(sm + S_PART);
    float* const red = reinterpret_cast<float*>(sm + S_RED);
    float* const inbox = reinterpret_cast<float*>(sm + S_IN);
    uint32_t* mail;
    asm volatile("mov.u64 %0, %1;" : "=l"(mail) : "l"(g_mail));
    STAMP(0);

    uint4 ldv = make_uint4(0u, 0u, 0u, 0u);
    if (tid < 72) ldv = *reinterpret_cast<const uint4*>(p.x + tid * 8);
    else if (tid >= 128 && tid < 200) ldv = *reinterpret_cast<const uint4*>(p.c + (tid - 128) * 8);
    else if (tid == 255) asm volatile("ld.relaxed.gpu.global.b32 %0, [%1];" : "=r"(ldv.x) : "l"(&g_count) : "memory");
    if (lane == 0) {
        constexpr int NB = N_BARS - P_KV, Q = (NB + 7) / 8;
        switch (wid) {
            case 0: init_bars<P_KV + 0 * Q, P_KV + 1 * Q>(bars); break;
            case 1: init_bars<P_KV + 1 * Q, P_KV + 2 * Q>(bars); break;
            case 2: init_bars<P_KV + 2 * Q, P_KV + 3 * Q>(bars); break;
            case 3: init_bars<P_KV + 3 * Q, P_KV + 4 * Q>(bars); break;
            case 4: init_bars<P_KV + 4 * Q, P_KV + 5 * Q>(bars); break;
            case 5: init_bars<P_KV + 5 * Q, P_KV + 6 * Q>(bars); break;
            case 6: init_bars<P_KV + 6 * Q, P_KV + 7 * Q>(bars); break;
            default:
                init_bars<P_KV + 7 * Q, N_BARS>(bars);
                static_assert(P_KV + 7 * Q <= BAR_DQ, "the last warp arms the exchange barriers");
                mbar_expect_tx(bars + 8 * BAR_DQ, CL * 1024);
                mbar_expect_tx(bars + 8 * BAR_DS, CL * 16);
                mbar_expect_tx(bars + 8 * BAR_DO, CL * 1024);
                mbar_expect_tx(bars + 8 * BAR_DX, CL * 384);
                mbar_expect_tx(bars + 8 * BAR_DH, CL * 1152);
                break;
        }
        asm volatile("fence.mbarrier_init.release.cluster;" ::: "memory");
        asm volatile("fence.proxy.async.shared::cta;" ::: "memory");
    }
    __syncwarp();
    asm volatile("bar.arrive 3, 288;" ::: "memory");
    asm volatile("barrier.cluster.arrive.relaxed.aligned;" ::: "memory");
    if (tid < 96) { st_word(mail + MB_P1 + b * 96 + tid, 0u); st_word(mail + MB_P2 + b * 96 + tid, 0u); }
    if (tid >= 96 && tid < 136) st_word(mail + MB_MOD + b * 40 + tid - 96, 0u);
    if (tid < 72) {
        *reinterpret_cast<float4*>(xs + tid * 8) = make_float4(bf_lo(ldv.x), bf_hi(ldv.x), bf_lo(ldv.y), bf_hi(ldv.y));
        *reinterpret_cast<float4*>(xs + tid * 8 + 4) = make_float4(bf_lo(ldv.z), bf_hi(ldv.z), bf_lo(ldv.w), bf_hi(ldv.w));
    } else if (tid >= 128 && tid < 200) {
        const uint32_t w[4] = {ldv.x, ldv.y, ldv.z, ldv.w};
        uint32_t o[4];
#pragma unroll
        for (int j = 0; j < 4; j++) {
            const float lo = bf_lo(w[j]), hi = bf_hi(w[j]);
            o[j] = pack2(lo * rcp(1.0f + ex2(-lo * LOG2E)), hi * rcp(1.0f + ex2(-hi * LOG2E)));
        }
        *reinterpret_cast<uint4*>(sm + S_P + (tid - 128) * 16) = make_uint4(o[0], o[1], o[2], o[3]);
    } else if (tid == 255) {
        reinterpret_cast<uint32_t*>(sm + S_MISC)[0] = ldv.x;
    }
    asm volatile("bar.sync 2, 288;" ::: "memory");
    const uint32_t cnt = reinterpret_cast<const uint32_t*>(sm + S_MISC)[0];
    const uint32_t tag = 1u + cnt;

    const int pc = (wid < 6 ? wid : 0) * 4 + t4;
    const float4 xown = *reinterpret_cast<const float4*>(xs + r * 96 + pc * 4);
    float xn[4] = {0.f, 0.f, 0.f, 0.f};
    if (wid == 0) {
        float mean_b, inv_den;
        ln_stats(xs, lane, mean_b, inv_den);
        const float4 v = *reinterpret_cast<const float4*>(xs + r * 96 + (lane < 24 ? lane : 0) * 4);
        xn[0] = rbf(rbf(v.x - mean_b) * inv_den); xn[1] = rbf(rbf(v.y - mean_b) * inv_den);
        xn[2] = rbf(rbf(v.z - mean_b) * inv_den); xn[3] = rbf(rbf(v.w - mean_b) * inv_den);
    }
    asm volatile("barrier.cluster.wait.acquire.aligned;" ::: "memory");

    uint32_t rb[CL];
#pragma unroll
    for (int d = 0; d < CL; d++) rb[d] = mapa(sb, d);
    const int ca_off = (r & 1) * 32, cb_off = (r & 1) ? 0 : 64;
    const int cm_w = wid < 4 ? wid * 16 + ca_off : (wid - 4) * 16 + cb_off;
    float acc[6][4];
#pragma unroll 1
    for (int ph = 0; ph < 2; ph++) {
        if ((ph == 0) == (b < NP1)) {
#pragma unroll
            for (int m = 0; m < 3; m++) { acc[m][0] = acc[m][1] = acc[m][2] = acc[m][3] = 0.f; }
            const uint32_t base = sb + OFF_M + (wid * 16 + (mi >> 1) * 8 + l7) * 80 + (mi & 1) * 16;
#pragma unroll
            for (int i = 0; i < 5; i++) {
                const int s = wid + 8 * i;
                if (i < 4 || wid < 4) {
                    const uint32_t b0 = lds32(sb + S_P + (s * 16 + 2 * t4) * 2), b1 = lds32(sb + S_P + (s * 16 + 8 + 2 * t4) * 2);
                    mbar_wait(bars + 8 * (pos_m + s / 6));
#pragma unroll
                    for (int m = 0; m < 3; m++) {
                        uint32_t a[4];
                        ldsm4t(a, base + i * (128 * 80) + m * 32);
                        mma16816(acc[m], a, b0, b1);
                    }
                }
            }
            if (t4 == 0) {
#pragma unroll
                for (int m = 0; m < 3; m++) { part[wid * 48 + m * 16 + gq] = acc[m][0]; part[wid * 48 + m * 16 + 8 + gq] = acc[m][2]; }
            }
            cbar();
            if (tid < 40) {
                const float* pp = part + tid;
                float m = rbf(((pp[0] + pp[48]) + (pp[96] + pp[144])) + ((pp[192] + pp[240]) + (pp[288] + pp[336])));
                const int u = tid - (b & 1) * 4;
                const int col = b * 36 + u;
                if ((col >= 576 && col < 1152) || (col >= 2304 && col < 2880)) m = rbf(1.0f + m);
                st_word(mail + MB_MOD + b * 40 + (u >= 0 && u < 36 ? u : (u < 0 ? u + 40 : u)), word_bf(m, tag));
            }
            STAMP(1);
            cbar();
        }
        if (ph == 1) break;

        if (tid < 24) {
            uint4 sa, ca;
            poll_pkt2(mail + mod_word(r * 96 + tid * 4), mail + mod_word(576 + r * 96 + tid * 4), tag, sa, ca);
            const float h0 = rbf(xn[0] * bf_hi(ca.x)) + bf_hi(sa.x), h1 = rbf(xn[1] * bf_hi(ca.y)) + bf_hi(sa.y);
            const float h2 = rbf(xn[2] * bf_hi(ca.z)) + bf_hi(sa.z), h3 = rbf(xn[3] * bf_hi(ca.w)) + bf_hi(sa.w);
            *reinterpret_cast<uint2*>(sm + S_H + tid * 8) = make_uint2(pack2(h0, h1), pack2(h2, h3));
        }
        cbar();
        STAMP(2);

        const int cb = wid >> 1;
        mbar_wait2(bars + 8 * (pos_q + 2 * cb), bars + 8 * (pos_q + 2 * cb + 1));
        float c0[4] = {0.f, 0.f, 0.f, 0.f}, c1[4] = {0.f, 0.f, 0.f, 0.f};
#pragma unroll
        for (int s = 0; s < 6; s++) {
            const int row = s * 16 + (mi >> 1) * 8 + l7;
            const uint32_t ra = sb + OFF_Q + cb * 12288 + row * 128;
            const int ch = (wid & 1) * 4 + (mi & 1);
            uint32_t a0[4], a1[4];
            ldsm4t(a0, ra + ((ch ^ l7) << 4));
            ldsm4t(a1, ra + (((ch + 2) ^ l7) << 4));
            const uint32_t b0 = lds32(sb + S_H + (s * 16 + 2 * t4) * 2), b1 = lds32(sb + S_H + (s * 16 + 8 + 2 * t4) * 2);
            mma16816(c0, a0, b0, b1);
            mma16816(c1, a1, b0, b1);
        }
        const float v = (t4 & 2) ? ((t4 & 1) ? c1[2] : c1[0]) : ((t4 & 1) ? c0[2] : c0[0]);
        bcast_word(rb, S_IN + (r * 288 + wid * 32 + (t4 >> 1) * 16 + (t4 & 1) * 8 + gq) * 4, __float_as_uint(v), S_BARS + 8 * BAR_DQ);
        STAMP(3);
    }
    mbar_wait_cl(bars + 8 * BAR_DQ);
    {
        const float* in = inbox + tid;
        const float q = ((in[0] + in[288]) + (in[576] + in[864])) + (in[1152] + in[1440]);
        reinterpret_cast<uint16_t*>(sm + S_QS)[tid] = (uint16_t)pack2(q, 0.f);
    }
    cbar();
    STAMP(4);

    float sv[2][4];
    {
        uint32_t qb[8][2];
#pragma unroll
        for (int s = 0; s < 8; s++) {
            qb[s][0] = lds32(sb + S_QS + ((gq & 1) * 128 + s * 16 + 2 * t4) * 2);
            qb[s][1] = lds32(sb + S_QS + ((gq & 1) * 128 + s * 16 + 8 + 2 * t4) * 2);
        }
#pragma unroll
        for (int e = 0; e < 4; e++) sv[0][e] = sv[1][e] = -INFINITY;
#pragma unroll
        for (int i = 0; i < 3; i++) {
            const int j = wid + 8 * i;
            if (j < nt) {
                const int slot = j < 2 ? j + 12 : (j < 16 ? j - 2 : j - 16);
                const uint32_t base = sb + OFF_X + slot * 8192;
                mbar_wait(bars + 8 * (P_KV + j));
                float c[2][4] = {{0.f, 0.f, 0.f, 0.f}, {0.f, 0.f, 0.f, 0.f}};
#pragma unroll
                for (int s = 0; s < 8; s++) {
#pragma unroll
                    for (int m = 0; m < 2; m++) {
                        const int row = m * 16 + (mi & 1) * 8 + l7;
                        const int ch = 2 * (s & 3) + (mi >> 1);
                        uint32_t a[4];
                        ldsm4(a, base + (s >> 2) * 4096 + row * 128 + ((ch ^ l7) << 4));
                        mma16816(c[m], a, qb[s][0], qb[s][1]);
                    }
                }
                __syncwarp();
                if (lane == 0) mbar_arrive(bars + 8 * (BAR_CK + j));
#pragma unroll
                for (int m = 0; m < 2; m++) {
                    if (t4 == ((i * 2 + m) & 3)) {
#pragma unroll
                        for (int e = 0; e < 4; e++) sv[i >> 1][e] = rbf(rbf(c[m][e]) * 0.08838834764831845f);
                    }
                }
            }
        }
    }
    STAMP(5);

    {
        float m0 = fmaxf(fmaxf(sv[0][0], sv[0][2]), fmaxf(sv[1][0], sv[1][2]));
        float m1 = fmaxf(fmaxf(sv[0][1], sv[0][3]), fmaxf(sv[1][1], sv[1][3]));
#pragma unroll
        for (int o = 16; o > 0; o >>= 1) {
            m0 = fmaxf(m0, __shfl_xor_sync(0xffffffffu, m0, o));
            m1 = fmaxf(m1, __shfl_xor_sync(0xffffffffu, m1, o));
        }
        if (lane == 0) { red[wid * 2] = m0; red[wid * 2 + 1] = m1; }
        cbar();
#pragma unroll
        for (int w = 0; w < 8; w++) { m0 = fmaxf(m0, red[w * 2]); m1 = fmaxf(m1, red[w * 2 + 1]); }
        uint16_t* P = reinterpret_cast<uint16_t*>(sm + S_P);
        float l0 = 0.f, l1 = 0.f;
#pragma unroll
        for (int h = 0; h < 2; h++) {
            const int j = wid + 8 * (2 * h + (t4 >> 1));
            if ((h == 0 || t4 < 2) && j < nt) {
                const float e0 = ex2((sv[h][0] - m0) * LOG2E), e1 = ex2((sv[h][1] - m1) * LOG2E);
                const float e2 = ex2((sv[h][2] - m0) * LOG2E), e3 = ex2((sv[h][3] - m1) * LOG2E);
                const int key = j * 32 + (t4 & 1) * 16 + gq;
                const uint32_t p01 = pack2(e0, e1), p23 = pack2(e2, e3);
                P[key] = (uint16_t)p01; P[key + 8] = (uint16_t)p23;
                P[PROW + key] = (uint16_t)(p01 >> 16); P[PROW + key + 8] = (uint16_t)(p23 >> 16);
                l0 += e0 + e2; l1 += e1 + e3;
            }
        }
#pragma unroll
        for (int o = 16; o > 0; o >>= 1) {
            l0 += __shfl_xor_sync(0xffffffffu, l0, o);
            l1 += __shfl_xor_sync(0xffffffffu, l1, o);
        }
        if (lane == 0) { red[16 + wid * 2] = l0; red[16 + wid * 2 + 1] = l1; }
        cbar();
        if (tid < 24) {
            const int dst = tid >> 2, e = tid & 3;
            float l = 0.f;
#pragma unroll
            for (int w = 0; w < 8; w++) l += red[16 + w * 2 + (e >> 1)];
            const float v = (e & 1) ? l : ((e >> 1) ? m1 : m0);
            st_async1(mapa(sb + S_ST + (r * 4 + e) * 4, dst), __float_as_uint(v), mapa(bars + 8 * BAR_DS, dst));
        }
    }
    STAMP(6);

    const uint32_t* modp;
    {
        const int t = tid < 96 ? tid : 0, v = t / 24, j = t - v * 24;
        modp = mail + mod_word((v == 0 ? 1152 : (v == 1 ? 2880 : (v == 2 ? 1728 : 2304))) + r * 96 + j * 4);
    }
    uint4 modw = make_uint4(0u, 0u, 0u, 0u);
    if (tid < 96) modw = ld_pkt(modp);

    {
        float c0[4] = {0.f, 0.f, 0.f, 0.f}, c1[4] = {0.f, 0.f, 0.f, 0.f};
        const uint32_t pb = sb + S_P + (gq & 1) * (PROW * 2) + t4 * 4;
        const int ch = 2 * (wid & 3) + (mi & 1);
        const uint32_t aoff = (wid >> 2) * 4096 + ((mi >> 1) * 8 + l7) * 128 + ((ch ^ l7) << 4);
        int slot = nt + 12 - 28;
#pragma unroll 1
        for (int j = 0; j < nt; j++) {
            const uint32_t base = sb + OFF_X + slot * 8192 + aoff;
            const uint32_t b0 = lds32(pb + j * 64), b1 = lds32(pb + j * 64 + 16);
            const uint32_t b2 = lds32(pb + j * 64 + 32), b3 = lds32(pb + j * 64 + 48);
            mbar_wait(bars + 8 * (P_KV + nt + j));
            uint32_t a0[4], a1[4];
            ldsm4t(a0, base);
            ldsm4t(a1, base + 2048);
            mma16816(c0, a0, b0, b1);
            mma16816(c1, a1, b2, b3);
            __syncwarp();
            if (lane == 0) mbar_arrive(bars + 8 * (BAR_CV + j));
            if (++slot == 14) slot = 0;
            if (j == 12 && wid == 0) {
                mbar_wait_cl(bars + 8 * BAR_DS);
                const int src = lane & 7, hh = (lane >> 3) & 1;
                const float2 st = *reinterpret_cast<const float2*>(sm + S_ST + ((src < CL ? src : 0) * 4 + hh * 2) * 4);
                const float m = src < CL ? st.x : -INFINITY;
                float M = m;
#pragma unroll
                for (int o = 1; o < 8; o <<= 1) M = fmaxf(M, __shfl_xor_sync(0xffffffffu, M, o));
                const float w = src < CL ? ex2((m - M) * LOG2E) : 0.f;
                float L = w * (src < CL ? st.y : 0.f);
#pragma unroll
                for (int o = 1; o < 8; o <<= 1) L += __shfl_xor_sync(0xffffffffu, L, o);
                if (lane < 16) reinterpret_cast<float*>(sm + S_F)[lane] = w * rcp(L);
            }
            if (j == 9 && tid < 96) {
                if (!pkt_ok(modw, tag)) modw = poll_pkt(modp, tag);
                *reinterpret_cast<float4*>(sm + S_G + tid * 16) = make_float4(bf_hi(modw.x), bf_hi(modw.y), bf_hi(modw.z), bf_hi(modw.w));
            }
            if (j == 13 && wid != 0) mbar_wait_cl(bars + 8 * BAR_DS);
        }
        const float v = (t4 & 2) ? ((t4 & 1) ? c0[3] + c1[3] : c0[2] + c1[2]) : ((t4 & 1) ? c0[1] + c1[1] : c0[0] + c1[0]);
        bcast_word(rb, S_IN + (r * 288 + (t4 & 1) * 128 + wid * 16 + gq + (t4 >> 1) * 8) * 4, __float_as_uint(v), S_BARS + 8 * BAR_DO);
    }
    STAMP(7);
    cbar();
    {
        const float* f = reinterpret_cast<const float*>(sm + S_F) + (tid >> 7) * 8;
        const float f0 = f[0], f1 = f[1], f2 = f[2], f3 = f[3], f4 = f[4], f5 = f[5];
        mbar_wait_cl(bars + 8 * BAR_DO);
        const float* in = inbox + tid;
        const float o = (fmaf(f0, in[0], f1 * in[288]) + fmaf(f2, in[576], f3 * in[864])) + fmaf(f4, in[1152], f5 * in[1440]);
        reinterpret_cast<uint16_t*>(sm + S_QS)[tid] = (uint16_t)pack2(o, 0.f);
    }
    cbar();
    STAMP(8);

    if (wid < 6) {
        uint32_t ob[8][4];
#pragma unroll
        for (int j = 0; j < 8; j++) ld_vec2(ob[j], sb + S_QS, j, mi);
        float c0[4] = {0.f, 0.f, 0.f, 0.f}, c1[4] = {0.f, 0.f, 0.f, 0.f};
        const int rl = (mi >> 1) * 8 + l7;
        const bool pa = wid < 4;
        const uint32_t base = pa ? sb + OFF_WOA + rl * 128 + (((2 * wid + (mi & 1)) ^ l7) << 4)
                                 : sb + OFF_WOB + rl * 64 + (((2 * (wid - 4) + (mi & 1)) ^ ((rl >> 1) & 3)) << 4);
        const uint32_t step = pa ? 16 * 128 : 16 * 64;
#pragma unroll
        for (int q = 0; q < 4; q++) {
            mbar_wait(bars + 8 * (pos_o + (pa ? pos_a(q) : pos_b(q >> 1))));
            uint32_t a[4][4];
#pragma unroll
            for (int i = 0; i < 4; i++) ldsm4t(a[i], base + (4 * q + i) * step);
            mma16816(c0, a[0], ob[2 * q][0], ob[2 * q][1]);
            mma16816(c1, a[1], ob[2 * q][2], ob[2 * q][3]);
            mma16816(c0, a[2], ob[2 * q + 1][0], ob[2 * q + 1][1]);
            mma16816(c1, a[3], ob[2 * q + 1][2], ob[2 * q + 1][3]);
        }
        if (t4 < 2)
            st_word(mail + MB_P1 + b * 96 + cm_w + t4 * 8 + gq, word_f32(t4 ? c0[2] + c1[2] : c0[0] + c1[0], tag));
    }
    STAMP(9);

    if (wid < 6) {
        const float4 ga = *reinterpret_cast<const float4*>(sm + S_G + pc * 16);
        const uint32_t* src = mail + MB_P1 + ((lane >> 2) * CL + r) * 96 + pc * 4;
        if (T_DELAY_G1 > 0) spin_cycles(T_DELAY_G1);
        if (T_LAT_G1 > 0) { const uint32_t tg = reinterpret_cast<const uint32_t*>(sm + S_MISC)[1]; for (int it = 0; (int)(gtime() - tg) < 0 && it < SPIN_LIMIT; it++) {} }
        uint4 u, w;
        if (T_GAP_G1 > 0) poll_pkt2_x2(src, src + 8 * CL * 96, tag, T_GAP_G1, u, w);
        else poll_pkt2(src, src + 8 * CL * 96, tag, u, w);
        float a0 = unword(u.x) + unword(w.x), a1 = unword(u.y) + unword(w.y);
        float a2 = unword(u.z) + unword(w.z), a3 = unword(u.w) + unword(w.w);
#pragma unroll
        for (int o = 4; o < 32; o <<= 1) {
            a0 += __shfl_xor_sync(0xffffffffu, a0, o);
            a1 += __shfl_xor_sync(0xffffffffu, a1, o);
            a2 += __shfl_xor_sync(0xffffffffu, a2, o);
            a3 += __shfl_xor_sync(0xffffffffu, a3, o);
        }
        a0 = rbf(xown.x + rbf(ga.x * rbf(a0))); a1 = rbf(xown.y + rbf(ga.y * rbf(a1)));
        a2 = rbf(xown.z + rbf(ga.z * rbf(a2))); a3 = rbf(xown.w + rbf(ga.w * rbf(a3)));
        if (gq < CL) st_async4(mapa(sb + S_X + (r * 96 + pc * 4) * 4, gq), a0, a1, a2, a3, mapa(bars + 8 * BAR_DX, gq));
    }
    STAMP(10);

    uint32_t w1f[3][6][4];
    {
        const uint32_t wb = bars + 8 * pos_w1;
        mbar_wait2(wb + 16 * (wid >> 2), wb + 16 * (wid >> 2) + 8);
        mbar_wait2(wb + 16 * (2 + (wid >> 2)), wb + 16 * (2 + (wid >> 2)) + 8);
        if (wid < 2) mbar_wait(wb + 64);
#pragma unroll
        for (int s = 0; s < 6; s++) {
            const int row = s * 16 + (mi >> 1) * 8 + l7;
            const uint32_t ra = sb + OFF_W1A + (wid >> 2) * 12288 + row * 128 + (((2 * (wid & 3) + (mi & 1)) ^ l7) << 4);
            ldsm4t(w1f[0][s], ra);
            ldsm4t(w1f[1][s], ra + 2 * 12288);
            if (wid < 2) ldsm4t(w1f[2][s], sb + OFF_W1B + row * 64 + (((2 * wid + (mi & 1)) ^ ((row >> 1) & 3)) << 4));
            else { w1f[2][s][0] = w1f[2][s][1] = w1f[2][s][2] = w1f[2][s][3] = 0u; }
        }
    }

    if (wid == 0) {
        const int j = lane < 24 ? lane : 0;
        const float4 sv2 = *reinterpret_cast<const float4*>(sm + S_G + 768 + j * 16);
        const float4 cb = *reinterpret_cast<const float4*>(sm + S_G + 1152 + j * 16);
        mbar_wait_cl(bars + 8 * BAR_DX);
        STAMP(11);
        const float4 v = *reinterpret_cast<const float4*>(xs + r * 96 + j * 4);
        float mean_b, inv_den;
        ln_stats(xs, lane, mean_b, inv_den);
        const float h0 = rbf(rbf(rbf(v.x - mean_b) * inv_den) * cb.x) + sv2.x;
        const float h1 = rbf(rbf(rbf(v.y - mean_b) * inv_den) * cb.y) + sv2.y;
        const float h2 = rbf(rbf(rbf(v.z - mean_b) * inv_den) * cb.z) + sv2.z;
        const float h3 = rbf(rbf(rbf(v.w - mean_b) * inv_den) * cb.w) + sv2.w;
        if (lane < 24) *reinterpret_cast<uint2*>(sm + S_H + lane * 8) = make_uint2(pack2(h0, h1), pack2(h2, h3));
    }
    cbar();
    STAMP(12);

    {
        uint32_t hb[6][2];
#pragma unroll
        for (int s = 0; s < 6; s++) { hb[s][0] = lds32(sb + S_H + (s * 16 + 2 * t4) * 2); hb[s][1] = lds32(sb + S_H + (s * 16 + 8 + 2 * t4) * 2); }
#pragma unroll
        for (int m = 0; m < 6; m++) { acc[m][0] = acc[m][1] = acc[m][2] = acc[m][3] = 0.f; }
#pragma unroll
        for (int s = 0; s < 6; s++) {
            mma16816(acc[(s & 1) * 3 + 0], w1f[0][s], hb[s][0], hb[s][1]);
            mma16816(acc[(s & 1) * 3 + 1], w1f[1][s], hb[s][0], hb[s][1]);
            if (wid < 2) mma16816(acc[(s & 1) * 3 + 2], w1f[2][s], hb[s][0], hb[s][1]);
        }
        const int ua = (g & 1) * 32, ub = (g & 1) ? 0 : 256;
        const float v = (t4 & 2) ? ((t4 & 1) ? acc[1][2] + acc[4][2] : acc[1][0] + acc[4][0]) : ((t4 & 1) ? acc[0][2] + acc[3][2] : acc[0][0] + acc[3][0]);
        bcast_word(rb, S_IN + (r * 288 + ua + (wid + (t4 >> 1) * 8) * 16 + (t4 & 1) * 8 + gq) * 4, __float_as_uint(v), S_BARS + 8 * BAR_DH);
        if (wid < 2 && t4 < 2)
            bcast_word(rb, S_IN + (r * 288 + ub + wid * 16 + t4 * 8 + gq) * 4,
                       __float_as_uint(t4 ? acc[2][2] + acc[5][2] : acc[2][0] + acc[5][0]), S_BARS + 8 * BAR_DH);
    }
    STAMP(13);

    if (wid >= 6) {
        mbar_wait_cl(bars + 8 * BAR_DH);
#pragma unroll
        for (int i = 0; i < 2; i++) {
            const int u = (tid - 192 + i * 64) * 4;
            if (u < 288) {
                const float* in = inbox + u;
                const float4 a0 = *reinterpret_cast<const float4*>(in), a1 = *reinterpret_cast<const float4*>(in + 288);
                const float4 a2 = *reinterpret_cast<const float4*>(in + 576), a3 = *reinterpret_cast<const float4*>(in + 864);
                const float4 a4 = *reinterpret_cast<const float4*>(in + 1152), a5 = *reinterpret_cast<const float4*>(in + 1440);
                const float t0 = rbf(((a0.x + a1.x) + (a2.x + a3.x)) + (a4.x + a5.x)), t1 = rbf(((a0.y + a1.y) + (a2.y + a3.y)) + (a4.y + a5.y));
                const float t2 = rbf(((a0.z + a1.z) + (a2.z + a3.z)) + (a4.z + a5.z)), t3 = rbf(((a0.w + a1.w) + (a2.w + a3.w)) + (a4.w + a5.w));
                *reinterpret_cast<uint2*>(sm + S_HV + u * 2) =
                    make_uint2(pack2(t0 * rcp(1.0f + ex2(-t0 * LOG2E)), t1 * rcp(1.0f + ex2(-t1 * LOG2E))),
                               pack2(t2 * rcp(1.0f + ex2(-t2 * LOG2E)), t3 * rcp(1.0f + ex2(-t3 * LOG2E))));
            }
        }
        cbar();
    } else {
        uint32_t w2f[18][4];
        const uint32_t wb = bars + 8 * pos_w2;
        const int rl = (mi >> 1) * 8 + l7;
        const bool pa = wid < 4;
        const uint32_t base = pa ? sb + OFF_W2A + rl * 128 + (((2 * wid + (mi & 1)) ^ l7) << 4)
                                 : sb + OFF_W2B + rl * 64 + (((2 * (wid - 4) + (mi & 1)) ^ ((rl >> 1) & 3)) << 4);
        const uint32_t step = pa ? 16 * 128 : 16 * 64;
#pragma unroll
        for (int q = 0; q < 5; q++) {
            mbar_wait(wb + 8 * (pa ? pos_a(q) : pos_b(q >> 1)));
#pragma unroll
            for (int i = 0; i < 3; i++) ldsm4t(w2f[3 * q + i], base + (3 * q + i) * step);
        }
        const uint32_t last = wb + 8 * (pa ? pos_a(5) : pos_b(2));
        const bool pre = mbar_test(last);
        if (pre) {
#pragma unroll
            for (int i = 0; i < 3; i++) ldsm4t(w2f[15 + i], base + (15 + i) * step);
        }
        cbar();
        STAMP(21);
        uint32_t vb[9][4];
#pragma unroll
        for (int j = 0; j < 9; j++) ld_vec2(vb[j], sb + S_HV, j, mi);
        float c[3][4];
#pragma unroll
        for (int i = 0; i < 3; i++) { c[i][0] = c[i][1] = c[i][2] = c[i][3] = 0.f; }
#pragma unroll
        for (int s = 0; s < 15; s++) mma16816(c[s % 3], w2f[s], vb[s >> 1][2 * (s & 1)], vb[s >> 1][2 * (s & 1) + 1]);
        if (!pre) {
            mbar_wait(last);
#pragma unroll
            for (int i = 0; i < 3; i++) ldsm4t(w2f[15 + i], base + (15 + i) * step);
        }
#pragma unroll
        for (int s = 15; s < 18; s++) mma16816(c[s % 3], w2f[s], vb[s >> 1][2 * (s & 1)], vb[s >> 1][2 * (s & 1) + 1]);
        if (t4 < 2)
            st_word(mail + MB_P2 + b * 96 + cm_w + t4 * 8 + gq,
                    word_f32(t4 ? (c[0][2] + c[1][2]) + c[2][2] : (c[0][0] + c[1][0]) + c[2][0], tag));
    }
    STAMP(14);

    if (g < 12 && wid == 0) {
        const int col = g * 8 + (lane & 1) * 4;
        const float4 gb = *reinterpret_cast<const float4*>(sm + S_G + 384 + col * 4);
        const float4 x2 = *reinterpret_cast<const float4*>(xs + r * 96 + col);
        if (T_DELAY_G2 > 0) spin_cycles(T_DELAY_G2);
        if (T_LAT_G2 > 0) { const uint32_t tg = reinterpret_cast<const uint32_t*>(sm + S_MISC)[2]; for (int it = 0; (int)(gtime() - tg) < 0 && it < SPIN_LIMIT; it++) {} }
        const uint32_t* src = mail + MB_P2 + ((lane >> 1) * CL + r) * 96 + col;
        const uint4 u = T_GAP_G2 > 0 ? poll_pkt_x2(src, tag, T_GAP_G2) : poll_pkt(src, tag);
        float a0 = unword(u.x), a1 = unword(u.y), a2 = unword(u.z), a3 = unword(u.w);
#pragma unroll
        for (int o = 2; o < 32; o <<= 1) {
            a0 += __shfl_xor_sync(0xffffffffu, a0, o);
            a1 += __shfl_xor_sync(0xffffffffu, a1, o);
            a2 += __shfl_xor_sync(0xffffffffu, a2, o);
            a3 += __shfl_xor_sync(0xffffffffu, a3, o);
        }
        if (lane < 2) {
            const uint2 o = make_uint2(pack2(x2.x + rbf(gb.x * rbf(a0)), x2.y + rbf(gb.y * rbf(a1))),
                                       pack2(x2.z + rbf(gb.z * rbf(a2)), x2.w + rbf(gb.w * rbf(a3))));
            *reinterpret_cast<uint2*>(p.out + r * 96 + col) = o;
        }
        if (b == 0 && lane == 0) g_count = (cnt >= 2u) ? 0u : cnt + 1u;
    }
    STAMP(15);
}

typedef CUresult (*EncodeTiledFn)(CUtensorMap*, CUtensorMapDataType, cuuint32_t, void*, const cuuint64_t*, const cuuint64_t*,
                                  const cuuint32_t*, const cuuint32_t*, CUtensorMapInterleave, CUtensorMapSwizzle,
                                  CUtensorMapL2promotion, CUtensorMapFloatOOBfill);

void encode2d(EncodeTiledFn enc, CUtensorMap* m, const void* ptr, uint64_t cols, uint64_t rows, uint32_t bc, uint32_t br,
              CUtensorMapSwizzle sw) {
    cuuint64_t dims[2] = {cols, rows};
    cuuint64_t str[1] = {cols * 2};
    cuuint32_t box[2] = {bc, br};
    cuuint32_t es[2] = {1, 1};
    enc(m, CU_TENSOR_MAP_DATA_TYPE_BFLOAT16, 2, const_cast<void*>(ptr), dims, str, box, es, CU_TENSOR_MAP_INTERLEAVE_NONE, sw,
        CU_TENSOR_MAP_L2_PROMOTION_L2_128B, CU_TENSOR_MAP_FLOAT_OOB_FILL_NONE);
}
void encode_kv(EncodeTiledFn enc, CUtensorMap* m, const void* ptr) {
    cuuint64_t dims[3] = {64, 16ull * SK_, 2};
    cuuint64_t str[2] = {256, 128};
    cuuint32_t box[3] = {64, 32, 2};
    cuuint32_t es[3] = {1, 1, 1};
    enc(m, CU_TENSOR_MAP_DATA_TYPE_BFLOAT16, 3, const_cast<void*>(ptr), dims, str, box, es, CU_TENSOR_MAP_INTERLEAVE_NONE,
        CU_TENSOR_MAP_SWIZZLE_128B, CU_TENSOR_MAP_L2_PROMOTION_L2_128B, CU_TENSOR_MAP_FLOAT_OOB_FILL_NONE);
}

}

extern "C" void kernel_launch(void* const* d_in, const int* in_sizes, int n_in, void* d_out, int out_size) {
    (void)in_sizes; (void)n_in; (void)out_size;
    static EncodeTiledFn enc = nullptr;
    if (!enc) {
        void* fn = nullptr;
        cudaDriverEntryPointQueryResult qr;
        cudaGetDriverEntryPoint("cuTensorMapEncodeTiled", &fn, cudaEnableDefault, &qr);
        enc = (EncodeTiledFn)fn;
        cudaFuncSetAttribute(adaln_attn_mlp_decode_kernel, cudaFuncAttributeMaxDynamicSharedMemorySize, SMEM_BYTES);
    }
    Maps maps;
    encode2d(enc, &maps.wmod, d_in[9], 3456, 576, 40, 96, CU_TENSOR_MAP_SWIZZLE_NONE);
    encode2d(enc, &maps.wq, d_in[3], 4096, 576, 64, 48, CU_TENSOR_MAP_SWIZZLE_128B);
    encode_kv(enc, &maps.k, d_in[1]);
    encode_kv(enc, &maps.v, d_in[2]);
    encode2d(enc, &maps.woa, d_in[4], 576, 4096, 64, 64, CU_TENSOR_MAP_SWIZZLE_128B);
    encode2d(enc, &maps.wob, d_in[4], 576, 4096, 32, 128, CU_TENSOR_MAP_SWIZZLE_64B);
    encode2d(enc, &maps.w1a, d_in[6], F_, 576, 64, 48, CU_TENSOR_MAP_SWIZZLE_128B);
    encode2d(enc, &maps.w1b, d_in[6], F_, 576, 32, 96, CU_TENSOR_MAP_SWIZZLE_64B);
    encode2d(enc, &maps.w2a, d_in[7], 576, F_, 64, 48, CU_TENSOR_MAP_SWIZZLE_128B);
    encode2d(enc, &maps.w2b, d_in[7], 576, F_, 32, 96, CU_TENSOR_MAP_SWIZZLE_64B);
    Ptrs p;
    p.x = (const __nv_bfloat16*)d_in[0];
    p.c = (const __nv_bfloat16*)d_in[8];
    p.out = (__nv_bfloat16*)d_out;
    cudaLaunchConfig_t cfg = {};
    cfg.gridDim = dim3(NCTA);
    cfg.blockDim = dim3(NTHREADS);
    cfg.dynamicSmemBytes = SMEM_BYTES;
    cfg.stream = cudaStreamPerThread;
    cudaLaunchAttribute at[1];
    at[0].id = cudaLaunchAttributeClusterDimension;
    at[0].val.clusterDim.x = CL; at[0].val.clusterDim.y = 1; at[0].val.clusterDim.z = 1;
    cfg.attrs = at;
    cfg.numAttrs = 1;
    cudaLaunchKernelEx(&cfg, adaln_attn_mlp_decode_kernel, maps, p);
}
```

```cpp
#include <cuda_runtime.h>
#include <cuda_bf16.h>
#include <cuda.h>
#include <stdint.h>

namespace {

constexpr int SK_ = 65536, WIN_ = 4096, F_ = 4608;
constexpr int CL = 6, NCL = 16, NCTA = CL * NCL, NTHREADS = 288;
constexpr int NP1 = 32;

constexpr int P_KV = 14, N_ITEMS = 14 + 44 + 6 + 9 + 9;
constexpr int BAR_CK = N_ITEMS;
constexpr int BAR_CV = BAR_CK + 22;
constexpr int BAR_DQ = BAR_CV + 22;
constexpr int BAR_DS = BAR_DQ + 1, BAR_DO = BAR_DQ + 2, BAR_DX = BAR_DQ + 3, BAR_DH = BAR_DQ + 4;
constexpr int N_BARS = BAR_DQ + 5;
__host__ __device__ constexpr int pos_a(int j) { return j + (j + 1) / 2; }
__host__ __device__ constexpr int pos_b(int j) { return 1 + 3 * j; }

constexpr int OFF_WOA = 0;
constexpr int OFF_WOB = 32768;
constexpr int OFF_W1A = 49152;
constexpr int OFF_W1B = OFF_W1A + 49152;
constexpr int OFF_W2A = OFF_W1B + 6144;
constexpr int OFF_W2B = OFF_W2A + 36864;
constexpr int OFF_M = 0;
constexpr int OFF_Q = 46080;
constexpr int OFF_X = 95232;
constexpr int OFF_SMALL = OFF_X + 14 * 8192;
constexpr int S_BARS = OFF_SMALL;
constexpr int S_H = S_BARS + 1088;
constexpr int S_X = S_H + 192;
constexpr int S_IN = S_X + 2304;
constexpr int S_QS = S_IN + 6912;
constexpr int S_P = S_QS + 512;
constexpr int S_PART = S_P + 2848;
constexpr int S_RED = S_PART + 3072;
constexpr int S_ST = S_RED + 256;
constexpr int S_F = S_ST + 96;
constexpr int S_HV = S_F + 64;
constexpr int S_G = S_HV + 576;
constexpr int S_MISC = S_G + 1536;
constexpr int S_DESC = S_MISC + 32;
constexpr int SMEM_BYTES = S_DESC + 384;
static_assert(N_BARS * 8 <= 1088, "barriers");
static_assert(OFF_W2B + 18432 <= OFF_X + 8 * 8192, "late weights");
static_assert(SMEM_BYTES <= 232448, "smem");
constexpr int PROW = 712;

constexpr float RATE_KV = 3240.f;
constexpr float RATE_LATE = 3300.f;
constexpr int WIN_KV = 8, WIN_LATE = 8;
constexpr int NFIRST = 4;
constexpr int LATE_FROM = 18;
constexpr uint32_t P1_Q_STEP = 150;
constexpr uint32_t DELAY_G1 = 600;
constexpr uint32_t LAT_G1 = 1900;
constexpr uint32_t DELAY_G2 = 150, GAP_G2 = 300;
constexpr float BYTES_22 = 46080.f + 49152.f + 44 * 8192.f + 49152.f + 55296.f + 55296.f;
constexpr float BYTES_21 = BYTES_22 - 2 * 8192.f;
constexpr float BYTES_ALL = 2 * NCL * BYTES_22 + 4 * NCL * BYTES_21;

struct Maps { CUtensorMap wmod, wq, k, v, woa, wob, w1a, w1b, w2a, w2b; };
struct Ptrs {
    const __nv_bfloat16 *x, *c;
    __nv_bfloat16* out;
};

constexpr int MB_MOD = 0;
constexpr int MB_P1 = MB_MOD + NCTA * 40;
constexpr int MB_P2 = MB_P1 + NCTA * 96;
constexpr int MB_END = MB_P2 + NCTA * 96;
__device__ __align__(128) uint32_t g_mail[MB_END];
__device__ uint32_t g_count;

__device__ __forceinline__ uint32_t smem_u32(const void* p) { return (uint32_t)__cvta_generic_to_shared(p); }
__device__ __forceinline__ void mbar_init(uint32_t bar, uint32_t cnt) {
    asm volatile("mbarrier.init.shared::cta.b64 [%0], %1;" ::"r"(bar), "r"(cnt));
}
__device__ __forceinline__ void mbar_expect_tx(uint32_t bar, uint32_t bytes) {
    asm volatile("mbarrier.arrive.expect_tx.shared::cta.b64 _, [%0], %1;" ::"r"(bar), "r"(bytes) : "memory");
}
__device__ __forceinline__ void mbar_arrive(uint32_t bar) {
    asm volatile("mbarrier.arrive.shared::cta.b64 _, [%0];" ::"r"(bar) : "memory");
}
constexpr int SPIN_LIMIT = 1 << 18;
__device__ __forceinline__ uint32_t mbar_try(uint32_t bar) {
    uint32_t ok;
    asm volatile("{\n.reg .pred p;\nmbarrier.try_wait.parity.shared::cta.b64 p, [%1], 0;\nselp.u32 %0, 1, 0, p;\n}"
                 : "=r"(ok) : "r"(bar) : "memory");
    return ok;
}
__device__ __forceinline__ uint32_t mbar_test(uint32_t bar) {
    uint32_t ok;
    asm volatile("{\n.reg .pred p;\nmbarrier.test_wait.parity.shared::cta.b64 p, [%1], 0;\nselp.u32 %0, 1, 0, p;\n}"
                 : "=r"(ok) : "r"(bar) : "memory");
    return ok;
}
__device__ __forceinline__ void mbar_wait(uint32_t bar) {
    int it = 0;
    while (!mbar_try(bar) && ++it < SPIN_LIMIT) {}
}
__device__ __forceinline__ void mbar_wait2(uint32_t bar0, uint32_t bar1) {
    int it = 0;
    while (!(mbar_try(bar0) & mbar_try(bar1)) && ++it < SPIN_LIMIT) {}
}
__device__ __forceinline__ void mbar_wait_cl(uint32_t bar) {
    uint32_t ok;
    int it = 0;
    do {
        asm volatile("{\n.reg .pred p;\nmbarrier.try_wait.parity.acquire.cluster.shared::cta.b64 p, [%1], 0;\nselp.u32 %0, 1, 0, p;\n}"
                     : "=r"(ok) : "r"(bar) : "memory");
    } while (!ok && ++it < SPIN_LIMIT);
}
__device__ __forceinline__ uint32_t mapa(uint32_t a, uint32_t rank) {
    uint32_t d;
    asm("mapa.shared::cluster.u32 %0, %1, %2;" : "=r"(d) : "r"(a), "r"(rank));
    return d;
}
__device__ __forceinline__ void st_async1(uint32_t dst, uint32_t v, uint32_t bar) {
    asm volatile("st.async.weak.shared::cluster.mbarrier::complete_tx::bytes.b32 [%0], %1, [%2];" ::"r"(dst), "r"(v), "r"(bar) : "memory");
}
__device__ __forceinline__ void st_async4(uint32_t dst, float a, float b, float c, float d, uint32_t bar) {
    asm volatile("st.async.weak.shared::cluster.mbarrier::complete_tx::bytes.v4.f32 [%0], {%1, %2, %3, %4}, [%5];"
                 ::"r"(dst), "f"(a), "f"(b), "f"(c), "f"(d), "r"(bar) : "memory");
}
__device__ __forceinline__ void bcast_word(const uint32_t (&rb)[CL], uint32_t off, uint32_t v, uint32_t bar_off) {
#pragma unroll
    for (int d = 0; d < CL; d++) st_async1(rb[d] + off, v, rb[d] + bar_off);
}
__device__ __forceinline__ void tma2d(uint32_t dst, const CUtensorMap* m, int c0, int c1, uint32_t bar) {
    asm volatile("cp.async.bulk.tensor.2d.shared::cluster.global.mbarrier::complete_tx::bytes [%0], [%1, {%3, %4}], [%2];"
                 ::"r"(dst), "l"(m), "r"(bar), "r"(c0), "r"(c1) : "memory");
}
__device__ __forceinline__ void issue2d(uint32_t bar, uint32_t bytes, uint32_t dst, const CUtensorMap* m, int c0, int c1) {
    asm volatile("{\n.reg .pred p;\nelect.sync _|p, 0xffffffff;\n"
                 "@p mbarrier.arrive.expect_tx.shared::cta.b64 _, [%0], %1;\n"
                 "@p cp.async.bulk.tensor.2d.shared::cluster.global.mbarrier::complete_tx::bytes [%2], [%3, {%4, %5}], [%0];\n}"
                 ::"r"(bar), "r"(bytes), "r"(dst), "l"(m), "r"(c0), "r"(c1) : "memory");
}
__device__ __forceinline__ void issue3d(uint32_t bar, uint32_t dst, const CUtensorMap* m, int row, uint64_t pol) {
    asm volatile("{\n.reg .pred p;\nelect.sync _|p, 0xffffffff;\n"
                 "@p mbarrier.arrive.expect_tx.shared::cta.b64 _, [%0], 8192;\n"
                 "@p cp.async.bulk.tensor.3d.shared::cluster.global.mbarrier::complete_tx::bytes.L2::cache_hint [%1], [%2, {0, %3, 0}], [%0], %4;\n}"
                 ::"r"(bar), "r"(dst), "l"(m), "r"(row), "l"(pol) : "memory");
}
__device__ __forceinline__ void ldsm4(uint32_t (&r)[4], uint32_t a) {
    asm volatile("ldmatrix.sync.aligned.m8n8.x4.shared.b16 {%0, %1, %2, %3}, [%4];"
                 : "=r"(r[0]), "=r"(r[1]), "=r"(r[2]), "=r"(r[3]) : "r"(a) : "memory");
}
__device__ __forceinline__ void ldsm4t(uint32_t (&r)[4], uint32_t a) {
    asm volatile("ldmatrix.sync.aligned.m8n8.x4.trans.shared.b16 {%0, %1, %2, %3}, [%4];"
                 : "=r"(r[0]), "=r"(r[1]), "=r"(r[2]), "=r"(r[3]) : "r"(a) : "memory");
}
__device__ __forceinline__ void mma16816(float (&c)[4], const uint32_t (&a)[4], uint32_t b0, uint32_t b1) {
    asm volatile("mma.sync.aligned.m16n8k16.row.col.f32.bf16.bf16.f32 {%0, %1, %2, %3}, {%4, %5, %6, %7}, {%8, %9}, {%0, %1, %2, %3};"
                 : "+f"(c[0]), "+f"(c[1]), "+f"(c[2]), "+f"(c[3])
                 : "r"(a[0]), "r"(a[1]), "r"(a[2]), "r"(a[3]), "r"(b0), "r"(b1));
}
__device__ __forceinline__ uint32_t lds32(uint32_t a) {
    uint32_t v;
    asm volatile("ld.shared.b32 %0, [%1];" : "=r"(v) : "r"(a) : "memory");
    return v;
}
__device__ __forceinline__ void cbar() { asm volatile("bar.sync 1, 256;" ::: "memory"); }

__device__ __forceinline__ void st_word(uint32_t* p, uint32_t v) {
    asm volatile("st.relaxed.gpu.global.b32 [%0], %1;" ::"l"(p), "r"(v) : "memory");
}
__device__ __forceinline__ uint4 ld_pkt(const uint32_t* p) {
    uint4 v;
    asm volatile("ld.relaxed.gpu.global.v4.b32 {%0, %1, %2, %3}, [%4];"
                 : "=r"(v.x), "=r"(v.y), "=r"(v.z), "=r"(v.w) : "l"(p) : "memory");
    return v;
}
__device__ __forceinline__ bool pkt_ok(const uint4& v, uint32_t tag) {
    return (((v.x ^ tag) | (v.y ^ tag) | (v.z ^ tag) | (v.w ^ tag)) & 3u) == 0u;
}
template <class T> __device__ __forceinline__ void pin(T*& p) { asm volatile("" : "+l"(p)); }
__device__ __forceinline__ void spin_cycles(uint32_t n) {
    uint32_t c0, c1;
    asm volatile("mov.u32 %0, %%clock;" : "=r"(c0));
    do { asm volatile("mov.u32 %0, %%clock;" : "=r"(c1)); } while (c1 - c0 < n);
}
__device__ __forceinline__ uint4 poll_pkt(const uint32_t* p, uint32_t tag) {
    uint4 v;
    int it = 0;
    do { v = ld_pkt(p); } while (!pkt_ok(v, tag) && ++it < SPIN_LIMIT);
    return v;
}
__device__ __forceinline__ void poll_pkt2(const uint32_t* p, const uint32_t* q, uint32_t tag, uint4& v, uint4& w) {
    int it = 0;
    do { v = ld_pkt(p); w = ld_pkt(q); } while (!(pkt_ok(v, tag) && pkt_ok(w, tag)) && ++it < SPIN_LIMIT);
}
__device__ __forceinline__ uint4 poll_pkt_x2(const uint32_t* p, uint32_t tag, uint32_t gap) {
    uint4 a = ld_pkt(p);
    spin_cycles(gap);
    uint4 c = ld_pkt(p);
    for (int it = 0; it < SPIN_LIMIT; it++) {
        if (pkt_ok(a, tag)) return a;
        a = ld_pkt(p);
        if (pkt_ok(c, tag)) return c;
        c = ld_pkt(p);
    }
    return a;
}
__device__ __forceinline__ uint32_t pack2(float lo, float hi) {
    uint32_t u;
    asm("cvt.rn.bf16x2.f32 %0, %1, %2;" : "=r"(u) : "f"(hi), "f"(lo));
    return u;
}
__device__ __forceinline__ float rbf(float x) { return __uint_as_float(pack2(0.f, x)); }
__device__ __forceinline__ float ex2(float x) { float y; asm("ex2.approx.ftz.f32 %0, %1;" : "=f"(y) : "f"(x)); return y; }
__device__ __forceinline__ float rcp(float x) { float y; asm("rcp.approx.ftz.f32 %0, %1;" : "=f"(y) : "f"(x)); return y; }
__device__ __forceinline__ float sqrt_a(float x) { float y; asm("sqrt.approx.ftz.f32 %0, %1;" : "=f"(y) : "f"(x)); return y; }
constexpr float LOG2E = 1.4426950408889634f;
__device__ __forceinline__ uint32_t word_bf(float x_rounded, uint32_t tag) { return __float_as_uint(x_rounded) | tag; }
__device__ __forceinline__ uint32_t word_f32(float x, uint32_t tag) { return (__float_as_uint(x) & ~3u) | tag; }
__device__ __forceinline__ float unword(uint32_t w) { return __uint_as_float(w & ~3u); }
__device__ __forceinline__ float bf_lo(uint32_t w) { return __uint_as_float(w << 16); }
__device__ __forceinline__ float bf_hi(uint32_t w) { return __uint_as_float(w & 0xFFFF0000u); }
__device__ __forceinline__ uint32_t gtime() { unsigned long long t; asm volatile("mov.u64 %0, %%globaltimer;" : "=l"(t)); return (uint32_t)t; }
__device__ __forceinline__ int mod_word(int c) { const int pb = c / 36; return MB_MOD + pb * 40 + (c - pb * 36); }

template <int LO, int HI>
__device__ __forceinline__ void init_bars(uint32_t bars) {
#pragma unroll
    for (int i = LO; i < HI; i++) mbar_init(bars + 8 * i, (i >= BAR_CV && i < BAR_DQ) ? 8 : 1);
}

__device__ __forceinline__ void ln_stats(const float* xs, int lane, float& mean_b, float& inv_den) {
    float v[18];
    const float c = xs[0];
#pragma unroll
    for (int i = 0; i < 4; i++) {
        const float4 a = *reinterpret_cast<const float4*>(xs + i * 128 + lane * 4);
        v[4 * i] = a.x; v[4 * i + 1] = a.y; v[4 * i + 2] = a.z; v[4 * i + 3] = a.w;
    }
    {
        const float2 a = *reinterpret_cast<const float2*>(xs + 512 + lane * 2);
        v[16] = a.x; v[17] = a.y;
    }
    float s0 = 0.f, s1 = 0.f, s2 = 0.f, q0 = 0.f, q1 = 0.f, q2 = 0.f;
#pragma unroll
    for (int i = 0; i < 18; i += 3) {
        const float d0 = v[i] - c, d1 = v[i + 1] - c, d2 = v[i + 2] - c;
        s0 += d0; s1 += d1; s2 += d2;
        q0 = fmaf(d0, d0, q0); q1 = fmaf(d1, d1, q1); q2 = fmaf(d2, d2, q2);
    }
    float s = (s0 + s1) + s2, q = (q0 + q1) + q2;
#pragma unroll
    for (int o = 16; o > 0; o >>= 1) {
        s += __shfl_xor_sync(0xffffffffu, s, o);
        q += __shfl_xor_sync(0xffffffffu, q, o);
    }
    const float md = s * (1.0f / 576.0f);
    const float var = fmaxf(fmaf(-md, md, q * (1.0f / 576.0f)), 0.f);
    mean_b = rbf(c + md);
    inv_den = rcp(rbf(sqrt_a(rbf(rbf(var) + 1e-5f))));
}

__device__ __forceinline__ void ld_vec2(uint32_t (&b)[4], uint32_t v, int j, int mi) { ldsm4(b, v + (4 * j + mi) * 16); }

__global__ void __launch_bounds__(NTHREADS, 1)
adaln_attn_mlp_decode_kernel(const __grid_constant__ Maps maps, const Ptrs p) {
    extern __shared__ __align__(1024) uint8_t sm[];
    const uint32_t sb = smem_u32(sm);
    int tid, b, r;
    asm volatile("mov.u32 %0, %%tid.x;" : "=r"(tid));
    asm volatile("mov.u32 %0, %%ctaid.x;" : "=r"(b));
    asm volatile("mov.u32 %0, %%cluster_ctarank;" : "=r"(r));
    const int g = b / CL;
    const int nt = 21 + (r < 2);
    const uint32_t bars = sb + S_BARS;
    const int pos_m = b < NP1 ? 0 : 8, pos_q = b < NP1 ? 6 : 0;
    const int pos_o = P_KV + 2 * nt, pos_w1 = pos_o + 6, pos_w2 = pos_w1 + 9;

    uint32_t t0 = 0;
    if (tid == 256) {
        t0 = gtime();
        if (sb & 1023u) __trap();
        init_bars<0, P_KV>(bars);
        asm volatile("fence.proxy.async.shared::cta;" ::: "memory");
        if (b < NP1) {
#pragma unroll
            for (int i = 0; i < 6; i++) {
                mbar_expect_tx(bars + 8 * i, 7680);
                tma2d(sb + OFF_M + i * 7680, &maps.wmod, b * 36 - (b & 1) * 4, i * 96, bars + 8 * i);
            }
        } else {
#pragma unroll
            for (int i = 0; i < NFIRST; i++) {
                mbar_expect_tx(bars + 8 * i, 6144);
                tma2d(sb + OFF_Q + i * 6144, &maps.wq, g * 256 + (i >> 1) * 64, r * 96 + (i & 1) * 48, bars + 8 * i);
            }
        }
    }

    if (tid >= 256) {
        if (tid > 256 && tid <= 256 + 24) {
            const int i = tid - 257;
            const int ca = r * 96 + (r & 1) * 32, cb = r * 96 + ((r & 1) ? 0 : 64);
            const int c1a = g * 288 + (g & 1) * 32, c1b = g * 288 + ((g & 1) ? 0 : 256);
            uint32_t dst, map; int c0, c1;
            if (i < 6) {
                const bool isb = (i == 1 || i == 4);
                const int j = isb ? (i >> 2) : (i == 0 ? 0 : (i == 5 ? 3 : i - 1));
                dst = isb ? OFF_WOB + j * 8192 : OFF_WOA + j * 8192; map = isb ? 5 : 4;
                c0 = isb ? cb : ca; c1 = g * 256 + j * (isb ? 128 : 64);
            } else if (i < 15) {
                const int j = i - 6;
                dst = j < 8 ? OFF_W1A + j * 6144 : OFF_W1B; map = j < 8 ? 6 : 7;
                c0 = j < 8 ? c1a + (j >> 1) * 64 : c1b; c1 = r * 96 + (j < 8 ? (j & 1) * 48 : 0);
            } else {
                const int k = i - 15, q = k / 3, m = k - 3 * q;
                const bool isb = m == 1;
                const int j = isb ? q : 2 * q + (m == 2);
                dst = isb ? OFF_W2B + j * 6144 : OFF_W2A + j * 6144; map = isb ? 9 : 8;
                c0 = isb ? cb : ca; c1 = g * 288 + j * (isb ? 96 : 48);
            }
            *reinterpret_cast<uint4*>(sm + S_DESC + i * 16) = make_uint4(sb + dst, map * 128u, (uint32_t)c0, (uint32_t)c1);
        }
        const float nsb_kv = (r < 2 ? BYTES_ALL / BYTES_22 : BYTES_ALL / BYTES_21) * (1.0f / RATE_KV);
        const float nsb_late = (r < 2 ? BYTES_ALL / BYTES_22 : BYTES_ALL / BYTES_21) * (1.0f / RATE_LATE);
        t0 = __shfl_sync(0xffffffffu, t0, 0);
        if (tid == 256) {
            const float t_wo = (46080.f + 49152.f + 8192.f * (nt + LATE_FROM)) * nsb_kv + 8192.f * (nt - LATE_FROM + 5) * nsb_late;
            reinterpret_cast<uint32_t*>(sm + S_MISC)[1] = t0 + (uint32_t)t_wo + LAT_G1;
        }
        __syncwarp();
        asm volatile("bar.arrive 2, 288;" ::: "memory");
        asm volatile("barrier.cluster.arrive.relaxed.aligned;" ::: "memory");
        uint64_t pol;
        asm volatile("createpolicy.fractional.L2::evict_first.b64 %0, 1.0;" : "=l"(pol));
        uint32_t tn = 0;
        uint32_t bar = bars;
        auto gate = [&](uint32_t wbar, uint32_t t) {
            uint32_t now = gtime();
            mbar_wait(wbar);
            for (int it = 0; now - t0 < t && it < SPIN_LIMIT; it++) now = gtime();
        };
        auto gate2 = [&](uint32_t wbar, uint32_t dep, uint32_t t) {
            uint32_t now = gtime();
            mbar_wait2(wbar, dep);
            for (int it = 0; now - t0 < t && it < SPIN_LIMIT; it++) now = gtime();
        };
        {
            const uint32_t st_m = (uint32_t)(7680.f * nsb_kv), st_q = (uint32_t)(6144.f * nsb_kv);
            const int q0 = b < NP1 ? 0 : NFIRST;
            bar += 8 * (b < NP1 ? 6 : NFIRST);
            tn += b < NP1 ? 6 * st_m : NFIRST * st_q;
#pragma unroll 1
            for (int i = q0; i < 8; i++) {
                const uint32_t wb = bar >= bars + 8 * WIN_KV ? bar - 8 * WIN_KV : bar;
                const uint32_t t = b < NP1 ? (uint32_t)P1_Q_STEP * (i + 1) : tn;
                if (wb != bar) gate(wb, t); else for (int it = 0; gtime() - t0 < t && it < SPIN_LIMIT; it++) {}
                issue2d(bar, 6144, sb + OFF_Q + i * 6144, &maps.wq, g * 256 + (i >> 1) * 64, r * 96 + (i & 1) * 48);
                bar += 8; tn += st_q;
            }
            if (b >= NP1) {
#pragma unroll 1
                for (int i = 0; i < 6; i++) {
                    gate(bar >= bars + 8 * WIN_KV ? bar - 8 * WIN_KV : bars, tn);
                    issue2d(bar, 7680, sb + OFF_M + i * 7680, &maps.wmod, b * 36 - (b & 1) * 4, i * 96);
                    bar += 8; tn += st_m;
                }
            }
        }
        asm volatile("bar.sync 3, 288;" ::: "memory");
        {
            const uint32_t st_kv = (uint32_t)(8192.f * nsb_kv), st_late8 = (uint32_t)(8192.f * nsb_late), st_late6 = (uint32_t)(6144.f * nsb_late);
            const int row0 = g * SK_ + (SK_ - WIN_) + (21 * r + (r < 2 ? r : 2)) * 32;
            uint32_t dst = sb + OFF_X + 12 * 8192;
            int row = row0;
#pragma unroll 1
            for (int i = 0; i < 14; i++) {
                gate(bar - 8 * WIN_KV, tn);
                issue3d(bar, dst, &maps.k, row, pol);
                bar += 8; tn += st_kv; row += 32;
                dst += 8192; if (dst == sb + OFF_X + 14 * 8192) dst = sb + OFF_X;
            }
            uint32_t cons = bars + 8 * BAR_CK;
#pragma unroll 1
            for (int i = 14; i < nt; i++) {
                gate2(bar - 8 * WIN_KV, cons, tn);
                issue3d(bar, dst, &maps.k, row, pol);
                bar += 8; cons += 8; tn += st_kv; row += 32;
                dst += 8192; if (dst == sb + OFF_X + 14 * 8192) dst = sb + OFF_X;
            }
            row = row0;
#pragma unroll 1
            for (int i = 0; i < nt; i++) {
                const bool late = i >= LATE_FROM;
                if (i == 14) cons = bars + 8 * BAR_CV;
                gate2(bar - 8 * (late ? WIN_LATE : WIN_KV), cons, tn);
                issue3d(bar, dst, &maps.v, row, pol);
                bar += 8; cons += 8; tn += late ? st_late8 : st_kv; row += 32;
                dst += 8192; if (dst == sb + OFF_X + 14 * 8192) dst = sb + OFF_X;
            }
            const uint32_t cv = bars + 8 * (BAR_CV + 30 - nt);
            const uint8_t* const mbase = reinterpret_cast<const uint8_t*>(&maps);
#pragma unroll 1
            for (int i = 0; i < 24; i++) {
                const uint4 d = *reinterpret_cast<const uint4*>(sm + S_DESC + i * 16);
                if (i == 13) mbar_wait2(cv, cv + 8);
                if (i == 15) { mbar_wait2(cv + 16, cv + 24); mbar_wait2(cv + 32, cv + 40); mbar_wait2(cv + 48, cv + 56); }
                gate(bar - 8 * WIN_LATE, tn);
                issue2d(bar, i < 6 ? 8192 : 6144, d.x, reinterpret_cast<const CUtensorMap*>(mbase + d.y), (int)d.z, (int)d.w);
                bar += 8; tn += i < 6 ? st_late8 : st_late6;
            }
        }
        return;
    }

    const int lane = tid & 31, wid = tid >> 5;
    const int gq = lane >> 2, t4 = lane & 3;
    const int mi = lane >> 3, l7 = lane & 7;
    float* const xs = reinterpret_cast<float*>(sm + S_X);
    float* const part = reinterpret_cast<float*>(sm + S_PART);
    float* const red = reinterpret_cast<float*>(sm + S_RED);
    float* const inbox = reinterpret_cast<float*>(sm + S_IN);
    uint32_t* mail;
    asm volatile("mov.u64 %0, %1;" : "=l"(mail) : "l"(g_mail));

    uint4 ldv = make_uint4(0u, 0u, 0u, 0u);
    if (tid < 72) ldv = *reinterpret_cast<const uint4*>(p.x + tid * 8);
    else if (tid >= 128 && tid < 200) ldv = *reinterpret_cast<const uint4*>(p.c + (tid - 128) * 8);
    else if (tid == 255) asm volatile("ld.relaxed.gpu.global.b32 %0, [%1];" : "=r"(ldv.x) : "l"(&g_count) : "memory");
    if (lane == 0) {
        constexpr int NB = N_BARS - P_KV, Q = (NB + 7) / 8;
        switch (wid) {
            case 0: init_bars<P_KV + 0 * Q, P_KV + 1 * Q>(bars); break;
            case 1: init_bars<P_KV + 1 * Q, P_KV + 2 * Q>(bars); break;
            case 2: init_bars<P_KV + 2 * Q, P_KV + 3 * Q>(bars); break;
            case 3: init_bars<P_KV + 3 * Q, P_KV + 4 * Q>(bars); break;
            case 4: init_bars<P_KV + 4 * Q, P_KV + 5 * Q>(bars); break;
            case 5: init_bars<P_KV + 5 * Q, P_KV + 6 * Q>(bars); break;
            case 6: init_bars<P_KV + 6 * Q, P_KV + 7 * Q>(bars); break;
            default:
                init_bars<P_KV + 7 * Q, N_BARS>(bars);
                static_assert(P_KV + 7 * Q <= BAR_DQ, "the last warp arms the exchange barriers");
                mbar_expect_tx(bars + 8 * BAR_DQ, CL * 1024);
                mbar_expect_tx(bars + 8 * BAR_DS, CL * 16);
                mbar_expect_tx(bars + 8 * BAR_DO, CL * 1024);
                mbar_expect_tx(bars + 8 * BAR_DX, CL * 384);
                mbar_expect_tx(bars + 8 * BAR_DH, CL * 1152);
                break;
        }
        asm volatile("fence.mbarrier_init.release.cluster;" ::: "memory");
        asm volatile("fence.proxy.async.shared::cta;" ::: "memory");
    }
    __syncwarp();
    asm volatile("bar.arrive 3, 288;" ::: "memory");
    asm volatile("barrier.cluster.arrive.relaxed.aligned;" ::: "memory");
    if (tid < 96) { st_word(mail + MB_P1 + b * 96 + tid, 0u); st_word(mail + MB_P2 + b * 96 + tid, 0u); }
    if (tid >= 96 && tid < 136) st_word(mail + MB_MOD + b * 40 + tid - 96, 0u);
    if (tid < 72) {
        *reinterpret_cast<float4*>(xs + tid * 8) = make_float4(bf_lo(ldv.x), bf_hi(ldv.x), bf_lo(ldv.y), bf_hi(ldv.y));
        *reinterpret_cast<float4*>(xs + tid * 8 + 4) = make_float4(bf_lo(ldv.z), bf_hi(ldv.z), bf_lo(ldv.w), bf_hi(ldv.w));
    } else if (tid >= 128 && tid < 200) {
        const uint32_t w[4] = {ldv.x, ldv.y, ldv.z, ldv.w};
        uint32_t o[4];
#pragma unroll
        for (int j = 0; j < 4; j++) {
            const float lo = bf_lo(w[j]), hi = bf_hi(w[j]);
            o[j] = pack2(lo * rcp(1.0f + ex2(-lo * LOG2E)), hi * rcp(1.0f + ex2(-hi * LOG2E)));
        }
        *reinterpret_cast<uint4*>(sm + S_P + (tid - 128) * 16) = make_uint4(o[0], o[1], o[2], o[3]);
    } else if (tid == 255) {
        reinterpret_cast<uint32_t*>(sm + S_MISC)[0] = ldv.x;
    }
    asm volatile("bar.sync 2, 288;" ::: "memory");
    const uint32_t cnt = reinterpret_cast<const uint32_t*>(sm + S_MISC)[0];
    const uint32_t tag = 1u + cnt;

    const int pc = (wid < 6 ? wid : 0) * 4 + t4;
    const float4 xown = *reinterpret_cast<const float4*>(xs + r * 96 + pc * 4);
    float xn[4] = {0.f, 0.f, 0.f, 0.f};
    if (wid == 0) {
        float mean_b, inv_den;
        ln_stats(xs, lane, mean_b, inv_den);
        const float4 v = *reinterpret_cast<const float4*>(xs + r * 96 + (lane < 24 ? lane : 0) * 4);
        xn[0] = rbf(rbf(v.x - mean_b) * inv_den); xn[1] = rbf(rbf(v.y - mean_b) * inv_den);
        xn[2] = rbf(rbf(v.z - mean_b) * inv_den); xn[3] = rbf(rbf(v.w - mean_b) * inv_den);
    }
    asm volatile("barrier.cluster.wait.acquire.aligned;" ::: "memory");

    uint32_t rb[CL];
#pragma unroll
    for (int d = 0; d < CL; d++) rb[d] = mapa(sb, d);
    const int ca_off = (r & 1) * 32, cb_off = (r & 1) ? 0 : 64;
    const int cm_w = wid < 4 ? wid * 16 + ca_off : (wid - 4) * 16 + cb_off;
    float acc[6][4];
#pragma unroll 1
    for (int ph = 0; ph < 2; ph++) {
        if ((ph == 0) == (b < NP1)) {
#pragma unroll
            for (int m = 0; m < 3; m++) { acc[m][0] = acc[m][1] = acc[m][2] = acc[m][3] = 0.f; }
            const uint32_t base = sb + OFF_M + (wid * 16 + (mi >> 1) * 8 + l7) * 80 + (mi & 1) * 16;
#pragma unroll
            for (int i = 0; i < 5; i++) {
                const int s = wid + 8 * i;
                if (i < 4 || wid < 4) {
                    const uint32_t b0 = lds32(sb + S_P + (s * 16 + 2 * t4) * 2), b1 = lds32(sb + S_P + (s * 16 + 8 + 2 * t4) * 2);
                    mbar_wait(bars + 8 * (pos_m + s / 6));
#pragma unroll
                    for (int m = 0; m < 3; m++) {
                        uint32_t a[4];
                        ldsm4t(a, base + i * (128 * 80) + m * 32);
                        mma16816(acc[m], a, b0, b1);
                    }
                }
            }
            if (t4 == 0) {
#pragma unroll
                for (int m = 0; m < 3; m++) { part[wid * 48 + m * 16 + gq] = acc[m][0]; part[wid * 48 + m * 16 + 8 + gq] = acc[m][2]; }
            }
            cbar();
            if (tid < 40) {
                const float* pp = part + tid;
                float m = rbf(((pp[0] + pp[48]) + (pp[96] + pp[144])) + ((pp[192] + pp[240]) + (pp[288] + pp[336])));
                const int u = tid - (b & 1) * 4;
                const int col = b * 36 + u;
                if ((col >= 576 && col < 1152) || (col >= 2304 && col < 2880)) m = rbf(1.0f + m);
                st_word(mail + MB_MOD + b * 40 + (u >= 0 && u < 36 ? u : (u < 0 ? u + 40 : u)), word_bf(m, tag));
            }
            cbar();
        }
        if (ph == 1) break;

        if (tid < 24) {
            uint4 sa, ca;
            poll_pkt2(mail + mod_word(r * 96 + tid * 4), mail + mod_word(576 + r * 96 + tid * 4), tag, sa, ca);
            const float h0 = rbf(xn[0] * bf_hi(ca.x)) + bf_hi(sa.x), h1 = rbf(xn[1] * bf_hi(ca.y)) + bf_hi(sa.y);
            const float h2 = rbf(xn[2] * bf_hi(ca.z)) + bf_hi(sa.z), h3 = rbf(xn[3] * bf_hi(ca.w)) + bf_hi(sa.w);
            *reinterpret_cast<uint2*>(sm + S_H + tid * 8) = make_uint2(pack2(h0, h1), pack2(h2, h3));
        }
        cbar();

        const int cb = wid >> 1;
        mbar_wait2(bars + 8 * (pos_q + 2 * cb), bars + 8 * (pos_q + 2 * cb + 1));
        float c0[4] = {0.f, 0.f, 0.f, 0.f}, c1[4] = {0.f, 0.f, 0.f, 0.f};
#pragma unroll
        for (int s = 0; s < 6; s++) {
            const int row = s * 16 + (mi >> 1) * 8 + l7;
            const uint32_t ra = sb + OFF_Q + cb * 12288 + row * 128;
            const int ch = (wid & 1) * 4 + (mi & 1);
            uint32_t a0[4], a1[4];
            ldsm4t(a0, ra + ((ch ^ l7) << 4));
            ldsm4t(a1, ra + (((ch + 2) ^ l7) << 4));
            const uint32_t b0 = lds32(sb + S_H + (s * 16 + 2 * t4) * 2), b1 = lds32(sb + S_H + (s * 16 + 8 + 2 * t4) * 2);
            mma16816(c0, a0, b0, b1);
            mma16816(c1, a1, b0, b1);
        }
        const float v = (t4 & 2) ? ((t4 & 1) ? c1[2] : c1[0]) : ((t4 & 1) ? c0[2] : c0[0]);
        bcast_word(rb, S_IN + (r * 288 + wid * 32 + (t4 >> 1) * 16 + (t4 & 1) * 8 + gq) * 4, __float_as_uint(v), S_BARS + 8 * BAR_DQ);
    }
    mbar_wait_cl(bars + 8 * BAR_DQ);
    {
        const float* in = inbox + tid;
        const float q = ((in[0] + in[288]) + (in[576] + in[864])) + (in[1152] + in[1440]);
        reinterpret_cast<uint16_t*>(sm + S_QS)[tid] = (uint16_t)pack2(q, 0.f);
    }
    cbar();

    float sv[2][4];
    {
        uint32_t qb[8][2];
#pragma unroll
        for (int s = 0; s < 8; s++) {
            qb[s][0] = lds32(sb + S_QS + ((gq & 1) * 128 + s * 16 + 2 * t4) * 2);
            qb[s][1] = lds32(sb + S_QS + ((gq & 1) * 128 + s * 16 + 8 + 2 * t4) * 2);
        }
#pragma unroll
        for (int e = 0; e < 4; e++) sv[0][e] = sv[1][e] = -INFINITY;
#pragma unroll
        for (int i = 0; i < 3; i++) {
            const int j = wid + 8 * i;
            if (j < nt) {
                const int slot = j < 2 ? j + 12 : (j < 16 ? j - 2 : j - 16);
                const uint32_t base = sb + OFF_X + slot * 8192;
                mbar_wait(bars + 8 * (P_KV + j));
                float c[2][4] = {{0.f, 0.f, 0.f, 0.f}, {0.f, 0.f, 0.f, 0.f}};
#pragma unroll
                for (int s = 0; s < 8; s++) {
#pragma unroll
                    for (int m = 0; m < 2; m++) {
                        const int row = m * 16 + (mi & 1) * 8 + l7;
                        const int ch = 2 * (s & 3) + (mi >> 1);
                        uint32_t a[4];
                        ldsm4(a, base + (s >> 2) * 4096 + row * 128 + ((ch ^ l7) << 4));
                        mma16816(c[m], a, qb[s][0], qb[s][1]);
                    }
                }
                __syncwarp();
                if (lane == 0) mbar_arrive(bars + 8 * (BAR_CK + j));
#pragma unroll
                for (int m = 0; m < 2; m++) {
                    if (t4 == ((i * 2 + m) & 3)) {
#pragma unroll
                        for (int e = 0; e < 4; e++) sv[i >> 1][e] = rbf(rbf(c[m][e]) * 0.08838834764831845f);
                    }
                }
            }
        }
    }

    {
        float m0 = fmaxf(fmaxf(sv[0][0], sv[0][2]), fmaxf(sv[1][0], sv[1][2]));
        float m1 = fmaxf(fmaxf(sv[0][1], sv[0][3]), fmaxf(sv[1][1], sv[1][3]));
#pragma unroll
        for (int o = 16; o > 0; o >>= 1) {
            m0 = fmaxf(m0, __shfl_xor_sync(0xffffffffu, m0, o));
            m1 = fmaxf(m1, __shfl_xor_sync(0xffffffffu, m1, o));
        }
        if (lane == 0) { red[wid * 2] = m0; red[wid * 2 + 1] = m1; }
        cbar();
#pragma unroll
        for (int w = 0; w < 8; w++) { m0 = fmaxf(m0, red[w * 2]); m1 = fmaxf(m1, red[w * 2 + 1]); }
        uint16_t* P = reinterpret_cast<uint16_t*>(sm + S_P);
        float l0 = 0.f, l1 = 0.f;
#pragma unroll
        for (int h = 0; h < 2; h++) {
            const int j = wid + 8 * (2 * h + (t4 >> 1));
            if ((h == 0 || t4 < 2) && j < nt) {
                const float e0 = ex2((sv[h][0] - m0) * LOG2E), e1 = ex2((sv[h][1] - m1) * LOG2E);
                const float e2 = ex2((sv[h][2] - m0) * LOG2E), e3 = ex2((sv[h][3] - m1) * LOG2E);
                const int key = j * 32 + (t4 & 1) * 16 + gq;
                const uint32_t p01 = pack2(e0, e1), p23 = pack2(e2, e3);
                P[key] = (uint16_t)p01; P[key + 8] = (uint16_t)p23;
                P[PROW + key] = (uint16_t)(p01 >> 16); P[PROW + key + 8] = (uint16_t)(p23 >> 16);
                l0 += e0 + e2; l1 += e1 + e3;
            }
        }
#pragma unroll
        for (int o = 16; o > 0; o >>= 1) {
            l0 += __shfl_xor_sync(0xffffffffu, l0, o);
            l1 += __shfl_xor_sync(0xffffffffu, l1, o);
        }
        if (lane == 0) { red[16 + wid * 2] = l0; red[16 + wid * 2 + 1] = l1; }
        cbar();
        if (tid < 24) {
            const int dst = tid >> 2, e = tid & 3;
            float l = 0.f;
#pragma unroll
            for (int w = 0; w < 8; w++) l += red[16 + w * 2 + (e >> 1)];
            const float v = (e & 1) ? l : ((e >> 1) ? m1 : m0);
            st_async1(mapa(sb + S_ST + (r * 4 + e) * 4, dst), __float_as_uint(v), mapa(bars + 8 * BAR_DS, dst));
        }
    }

    const uint32_t* modp;
    {
        const int t = tid < 96 ? tid : 0, v = t / 24, j = t - v * 24;
        modp = mail + mod_word((v == 0 ? 1152 : (v == 1 ? 2880 : (v == 2 ? 1728 : 2304))) + r * 96 + j * 4);
    }
    uint4 modw = make_uint4(0u, 0u, 0u, 0u);
    if (tid < 96) modw = ld_pkt(modp);

    {
        float c0[4] = {0.f, 0.f, 0.f, 0.f}, c1[4] = {0.f, 0.f, 0.f, 0.f};
        const uint32_t pb = sb + S_P + (gq & 1) * (PROW * 2) + t4 * 4;
        const int ch = 2 * (wid & 3) + (mi & 1);
        const uint32_t aoff = (wid >> 2) * 4096 + ((mi >> 1) * 8 + l7) * 128 + ((ch ^ l7) << 4);
        int slot = nt + 12 - 28;
#pragma unroll 1
        for (int j = 0; j < nt; j++) {
            const uint32_t base = sb + OFF_X + slot * 8192 + aoff;
            const uint32_t b0 = lds32(pb + j * 64), b1 = lds32(pb + j * 64 + 16);
            const uint32_t b2 = lds32(pb + j * 64 + 32), b3 = lds32(pb + j * 64 + 48);
            mbar_wait(bars + 8 * (P_KV + nt + j));
            uint32_t a0[4], a1[4];
            ldsm4t(a0, base);
            ldsm4t(a1, base + 2048);
            mma16816(c0, a0, b0, b1);
            mma16816(c1, a1, b2, b3);
            __syncwarp();
            if (lane == 0) mbar_arrive(bars + 8 * (BAR_CV + j));
            if (++slot == 14) slot = 0;
            if (j == 12 && wid == 0) {
                mbar_wait_cl(bars + 8 * BAR_DS);
                const int src = lane & 7, hh = (lane >> 3) & 1;
                const float2 st = *reinterpret_cast<const float2*>(sm + S_ST + ((src < CL ? src : 0) * 4 + hh * 2) * 4);
                const float m = src < CL ? st.x : -INFINITY;
                float M = m;
#pragma unroll
                for (int o = 1; o < 8; o <<= 1) M = fmaxf(M, __shfl_xor_sync(0xffffffffu, M, o));
                const float w = src < CL ? ex2((m - M) * LOG2E) : 0.f;
                float L = w * (src < CL ? st.y : 0.f);
#pragma unroll
                for (int o = 1; o < 8; o <<= 1) L += __shfl_xor_sync(0xffffffffu, L, o);
                if (lane < 16) reinterpret_cast<float*>(sm + S_F)[lane] = w * rcp(L);
            }
            if (j == 9 && tid < 96) {
                if (!pkt_ok(modw, tag)) modw = poll_pkt(modp, tag);
                *reinterpret_cast<float4*>(sm + S_G + tid * 16) = make_float4(bf_hi(modw.x), bf_hi(modw.y), bf_hi(modw.z), bf_hi(modw.w));
            }
            if (j == 13 && wid != 0) mbar_wait_cl(bars + 8 * BAR_DS);
        }
        const float v = (t4 & 2) ? ((t4 & 1) ? c0[3] + c1[3] : c0[2] + c1[2]) : ((t4 & 1) ? c0[1] + c1[1] : c0[0] + c1[0]);
        bcast_word(rb, S_IN + (r * 288 + (t4 & 1) * 128 + wid * 16 + gq + (t4 >> 1) * 8) * 4, __float_as_uint(v), S_BARS + 8 * BAR_DO);
    }
    uint32_t* p1_out = mail + MB_P1 + b * 96 + cm_w + (t4 & 1) * 8 + gq;
    const uint32_t* p1_in = mail + MB_P1 + ((lane >> 2) * CL + r) * 96 + pc * 4;
    uint32_t* p2_out = p1_out + (MB_P2 - MB_P1);
    pin(p1_out); pin(p1_in); pin(p2_out);
    cbar();
    {
        const float* f = reinterpret_cast<const float*>(sm + S_F) + (tid >> 7) * 8;
        const float f0 = f[0], f1 = f[1], f2 = f[2], f3 = f[3], f4 = f[4], f5 = f[5];
        mbar_wait_cl(bars + 8 * BAR_DO);
        const float* in = inbox + tid;
        const float o = (fmaf(f0, in[0], f1 * in[288]) + fmaf(f2, in[576], f3 * in[864])) + fmaf(f4, in[1152], f5 * in[1440]);
        reinterpret_cast<uint16_t*>(sm + S_QS)[tid] = (uint16_t)pack2(o, 0.f);
    }
    cbar();

    if (wid < 6) {
        uint32_t ob[8][4];
#pragma unroll
        for (int j = 0; j < 8; j++) ld_vec2(ob[j], sb + S_QS, j, mi);
        float c0[4] = {0.f, 0.f, 0.f, 0.f}, c1[4] = {0.f, 0.f, 0.f, 0.f};
        const int rl = (mi >> 1) * 8 + l7;
        const bool pa = wid < 4;
        const uint32_t base = pa ? sb + OFF_WOA + rl * 128 + (((2 * wid + (mi & 1)) ^ l7) << 4)
                                 : sb + OFF_WOB + rl * 64 + (((2 * (wid - 4) + (mi & 1)) ^ ((rl >> 1) & 3)) << 4);
        const uint32_t step = pa ? 16 * 128 : 16 * 64;
#pragma unroll
        for (int q = 0; q < 4; q++) {
            mbar_wait(bars + 8 * (pos_o + (pa ? pos_a(q) : pos_b(q >> 1))));
            uint32_t a[4][4];
#pragma unroll
            for (int i = 0; i < 4; i++) ldsm4t(a[i], base + (4 * q + i) * step);
            mma16816(c0, a[0], ob[2 * q][0], ob[2 * q][1]);
            mma16816(c1, a[1], ob[2 * q][2], ob[2 * q][3]);
            mma16816(c0, a[2], ob[2 * q + 1][0], ob[2 * q + 1][1]);
            mma16816(c1, a[3], ob[2 * q + 1][2], ob[2 * q + 1][3]);
        }
        if (t4 < 2) st_word(p1_out, word_f32(t4 ? c0[2] + c1[2] : c0[0] + c1[0], tag));
    }

    if (wid < 6) {
        const float4 ga = *reinterpret_cast<const float4*>(sm + S_G + pc * 16);
        spin_cycles(DELAY_G1);
        const uint32_t tg = reinterpret_cast<const uint32_t*>(sm + S_MISC)[1];
        for (int it = 0; (int)(gtime() - tg) < 0 && it < SPIN_LIMIT; it++) {}
        uint4 u, w;
        poll_pkt2(p1_in, p1_in + 8 * CL * 96, tag, u, w);
        float a0 = unword(u.x) + unword(w.x), a1 = unword(u.y) + unword(w.y);
        float a2 = unword(u.z) + unword(w.z), a3 = unword(u.w) + unword(w.w);
#pragma unroll
        for (int o = 4; o < 32; o <<= 1) {
            a0 += __shfl_xor_sync(0xffffffffu, a0, o);
            a1 += __shfl_xor_sync(0xffffffffu, a1, o);
            a2 += __shfl_xor_sync(0xffffffffu, a2, o);
            a3 += __shfl_xor_sync(0xffffffffu, a3, o);
        }
        a0 = rbf(xown.x + rbf(ga.x * rbf(a0))); a1 = rbf(xown.y + rbf(ga.y * rbf(a1)));
        a2 = rbf(xown.z + rbf(ga.z * rbf(a2))); a3 = rbf(xown.w + rbf(ga.w * rbf(a3)));
        if (gq < CL) st_async4(mapa(sb + S_X + (r * 96 + pc * 4) * 4, gq), a0, a1, a2, a3, mapa(bars + 8 * BAR_DX, gq));
    }

    uint32_t w1f[3][6][4];
    {
        const uint32_t wb = bars + 8 * pos_w1;
        mbar_wait2(wb + 16 * (wid >> 2), wb + 16 * (wid >> 2) + 8);
        mbar_wait2(wb + 16 * (2 + (wid >> 2)), wb + 16 * (2 + (wid >> 2)) + 8);
        if (wid < 2) mbar_wait(wb + 64);
#pragma unroll
        for (int s = 0; s < 6; s++) {
            const int row = s * 16 + (mi >> 1) * 8 + l7;
            const uint32_t ra = sb + OFF_W1A + (wid >> 2) * 12288 + row * 128 + (((2 * (wid & 3) + (mi & 1)) ^ l7) << 4);
            ldsm4t(w1f[0][s], ra);
            ldsm4t(w1f[1][s], ra + 2 * 12288);
            if (wid < 2) ldsm4t(w1f[2][s], sb + OFF_W1B + row * 64 + (((2 * wid + (mi & 1)) ^ ((row >> 1) & 3)) << 4));
            else { w1f[2][s][0] = w1f[2][s][1] = w1f[2][s][2] = w1f[2][s][3] = 0u; }
        }
    }

    if (wid == 0) {
        const int j = lane < 24 ? lane : 0;
        const float4 sv2 = *reinterpret_cast<const float4*>(sm + S_G + 768 + j * 16);
        const float4 cb = *reinterpret_cast<const float4*>(sm + S_G + 1152 + j * 16);
        mbar_wait_cl(bars + 8 * BAR_DX);
        const float4 v = *reinterpret_cast<const float4*>(xs + r * 96 + j * 4);
        float mean_b, inv_den;
        ln_stats(xs, lane, mean_b, inv_den);
        const float h0 = rbf(rbf(rbf(v.x - mean_b) * inv_den) * cb.x) + sv2.x;
        const float h1 = rbf(rbf(rbf(v.y - mean_b) * inv_den) * cb.y) + sv2.y;
        const float h2 = rbf(rbf(rbf(v.z - mean_b) * inv_den) * cb.z) + sv2.z;
        const float h3 = rbf(rbf(rbf(v.w - mean_b) * inv_den) * cb.w) + sv2.w;
        if (lane < 24) *reinterpret_cast<uint2*>(sm + S_H + lane * 8) = make_uint2(pack2(h0, h1), pack2(h2, h3));
    }
    cbar();

    {
        uint32_t hb[6][2];
#pragma unroll
        for (int j = 0; j < 3; j++) {
            uint32_t t[4];
            ld_vec2(t, sb + S_H, j, mi);
            hb[2 * j][0] = t[0]; hb[2 * j][1] = t[1]; hb[2 * j + 1][0] = t[2]; hb[2 * j + 1][1] = t[3];
        }
#pragma unroll
        for (int m = 0; m < 6; m++) { acc[m][0] = acc[m][1] = acc[m][2] = acc[m][3] = 0.f; }
#pragma unroll
        for (int s = 0; s < 6; s++) {
            mma16816(acc[(s & 1) * 3 + 0], w1f[0][s], hb[s][0], hb[s][1]);
            mma16816(acc[(s & 1) * 3 + 1], w1f[1][s], hb[s][0], hb[s][1]);
            if (wid < 2) mma16816(acc[(s & 1) * 3 + 2], w1f[2][s], hb[s][0], hb[s][1]);
        }
        const int ua = (g & 1) * 32, ub = (g & 1) ? 0 : 256;
        const float v = (t4 & 2) ? ((t4 & 1) ? acc[1][2] + acc[4][2] : acc[1][0] + acc[4][0]) : ((t4 & 1) ? acc[0][2] + acc[3][2] : acc[0][0] + acc[3][0]);
        bcast_word(rb, S_IN + (r * 288 + ua + (wid + (t4 >> 1) * 8) * 16 + (t4 & 1) * 8 + gq) * 4, __float_as_uint(v), S_BARS + 8 * BAR_DH);
        if (wid < 2 && t4 < 2)
            bcast_word(rb, S_IN + (r * 288 + ub + wid * 16 + t4 * 8 + gq) * 4,
                       __float_as_uint(t4 ? acc[2][2] + acc[5][2] : acc[2][0] + acc[5][0]), S_BARS + 8 * BAR_DH);
    }

    if (wid >= 6) {
        mbar_wait_cl(bars + 8 * BAR_DH);
        {
            const int t = tid - 192;
            const float* in = inbox + t * 4;
            const float* in2 = inbox + 256 + (t & 31);
            const float4 a0 = *reinterpret_cast<const float4*>(in), a1 = *reinterpret_cast<const float4*>(in + 288);
            const float4 a2 = *reinterpret_cast<const float4*>(in + 576), a3 = *reinterpret_cast<const float4*>(in + 864);
            const float4 a4 = *reinterpret_cast<const float4*>(in + 1152), a5 = *reinterpret_cast<const float4*>(in + 1440);
            const float e0 = in2[0], e1 = in2[288], e2 = in2[576], e3 = in2[864], e4 = in2[1152], e5 = in2[1440];
            const float t0 = rbf(((a0.x + a1.x) + (a2.x + a3.x)) + (a4.x + a5.x)), t1 = rbf(((a0.y + a1.y) + (a2.y + a3.y)) + (a4.y + a5.y));
            const float t2 = rbf(((a0.z + a1.z) + (a2.z + a3.z)) + (a4.z + a5.z)), t3 = rbf(((a0.w + a1.w) + (a2.w + a3.w)) + (a4.w + a5.w));
            const float t4v = rbf(((e0 + e1) + (e2 + e3)) + (e4 + e5));
            *reinterpret_cast<uint2*>(sm + S_HV + t * 8) =
                make_uint2(pack2(t0 * rcp(1.0f + ex2(-t0 * LOG2E)), t1 * rcp(1.0f + ex2(-t1 * LOG2E))),
                           pack2(t2 * rcp(1.0f + ex2(-t2 * LOG2E)), t3 * rcp(1.0f + ex2(-t3 * LOG2E))));
            const uint32_t hx = pack2(t4v * rcp(1.0f + ex2(-t4v * LOG2E)), 0.f);
            if (t < 32) reinterpret_cast<uint16_t*>(sm + S_HV)[256 + t] = (uint16_t)hx;
        }
        cbar();
    } else {
        uint32_t w2f[18][4];
        const uint32_t wb = bars + 8 * pos_w2;
        const int rl = (mi >> 1) * 8 + l7;
        const bool pa = wid < 4;
        const uint32_t base = pa ? sb + OFF_W2A + rl * 128 + (((2 * wid + (mi & 1)) ^ l7) << 4)
                                 : sb + OFF_W2B + rl * 64 + (((2 * (wid - 4) + (mi & 1)) ^ ((rl >> 1) & 3)) << 4);
        const uint32_t step = pa ? 16 * 128 : 16 * 64;
#pragma unroll
        for (int q = 0; q < 5; q++) {
            mbar_wait(wb + 8 * (pa ? pos_a(q) : pos_b(q >> 1)));
#pragma unroll
            for (int i = 0; i < 3; i++) ldsm4t(w2f[3 * q + i], base + (3 * q + i) * step);
        }
        const uint32_t last = wb + 8 * (pa ? pos_a(5) : pos_b(2));
        const bool pre = mbar_test(last);
        if (pre) {
#pragma unroll
            for (int i = 0; i < 3; i++) ldsm4t(w2f[15 + i], base + (15 + i) * step);
        }
        cbar();
        uint32_t vb[9][4];
#pragma unroll
        for (int j = 0; j < 9; j++) ld_vec2(vb[j], sb + S_HV, j, mi);
        float c[3][4];
#pragma unroll
        for (int i = 0; i < 3; i++) { c[i][0] = c[i][1] = c[i][2] = c[i][3] = 0.f; }
#pragma unroll
        for (int s = 0; s < 15; s++) mma16816(c[s % 3], w2f[s], vb[s >> 1][2 * (s & 1)], vb[s >> 1][2 * (s & 1) + 1]);
        if (!pre) {
            mbar_wait(last);
#pragma unroll
            for (int i = 0; i < 3; i++) ldsm4t(w2f[15 + i], base + (15 + i) * step);
        }
#pragma unroll
        for (int s = 15; s < 18; s++) mma16816(c[s % 3], w2f[s], vb[s >> 1][2 * (s & 1)], vb[s >> 1][2 * (s & 1) + 1]);
        if (t4 < 2) st_word(p2_out, word_f32(t4 ? (c[0][2] + c[1][2]) + c[2][2] : (c[0][0] + c[1][0]) + c[2][0], tag));
    }

    if (g < 12 && wid == 0) {
        const int col = g * 8 + (lane & 1) * 4;
        const float4 gb = *reinterpret_cast<const float4*>(sm + S_G + 384 + col * 4);
        const float4 x2 = *reinterpret_cast<const float4*>(xs + r * 96 + col);
        const uint32_t* src = mail + MB_P2 + ((lane >> 1) * CL + r) * 96 + col;
        spin_cycles(DELAY_G2);
        const uint4 u = poll_pkt_x2(src, tag, GAP_G2);
        float a0 = unword(u.x), a1 = unword(u.y), a2 = unword(u.z), a3 = unword(u.w);
#pragma unroll
        for (int o = 2; o < 32; o <<= 1) {
            a0 += __shfl_xor_sync(0xffffffffu, a0, o);
            a1 += __shfl_xor_sync(0xffffffffu, a1, o);
            a2 += __shfl_xor_sync(0xffffffffu, a2, o);
            a3 += __shfl_xor_sync(0xffffffffu, a3, o);
        }
        if (lane < 2) {
            const uint2 o = make_uint2(pack2(x2.x + rbf(gb.x * rbf(a0)), x2.y + rbf(gb.y * rbf(a1))),
                                       pack2(x2.z + rbf(gb.z * rbf(a2)), x2.w + rbf(gb.w * rbf(a3))));
            *reinterpret_cast<uint2*>(p.out + r * 96 + col) = o;
        }
        if (b == 0 && lane == 0) g_count = (cnt >= 2u) ? 0u : cnt + 1u;
    }
}

__device__ float fb_mod[3456], fb_q[4096], fb_o[4096], fb_x2[576], fb_hv[4608];

__device__ __forceinline__ float ldbf(const __nv_bfloat16* p) { return __bfloat162float(*p); }
__device__ __forceinline__ float silu_fb(float v) { return v / (1.0f + expf(-v)); }
__device__ __forceinline__ float gemv_fb(const float* v, const __nv_bfloat16* W, int K, int N, int n) {
    float s = 0.f;
    for (int k = 0; k < K; k++) s = fmaf(v[k], ldbf(W + (size_t)k * N + n), s);
    return rbf(s);
}
__device__ void ln_mod_fb(const float* x, const float* scale, const float* shift, float* h) {
    float s = 0.f, q = 0.f;
    for (int i = 0; i < 576; i++) s += x[i];
    const float mean = s / 576.0f;
    for (int i = 0; i < 576; i++) q = fmaf(x[i] - mean, x[i] - mean, q);
    const float m = rbf(mean), den = rbf(sqrtf(rbf(rbf(q / 576.0f) + 1e-5f)));
    for (int i = threadIdx.x; i < 576; i += blockDim.x)
        h[i] = rbf(rbf(rbf(rbf(x[i] - m) / den) * rbf(1.0f + scale[i])) + shift[i]);
    __syncthreads();
}
__global__ void fb_mod_kernel(const __nv_bfloat16* c, const __nv_bfloat16* wmod) {
    __shared__ float v[576];
    for (int i = threadIdx.x; i < 576; i += blockDim.x) v[i] = rbf(silu_fb(ldbf(c + i)));
    __syncthreads();
    const int n = blockIdx.x * blockDim.x + threadIdx.x;
    fb_mod[n] = gemv_fb(v, wmod, 576, 3456, n);
}
__global__ void fb_q_kernel(const __nv_bfloat16* x, const __nv_bfloat16* wq) {
    __shared__ float xs[576], h[576];
    for (int i = threadIdx.x; i < 576; i += blockDim.x) xs[i] = ldbf(x + i);
    __syncthreads();
    ln_mod_fb(xs, fb_mod + 576, fb_mod, h);
    const int n = blockIdx.x * blockDim.x + threadIdx.x;
    fb_q[n] = gemv_fb(h, wq, 576, 4096, n);
}
__global__ void fb_attn_kernel(const __nv_bfloat16* K, const __nv_bfloat16* V) {
    __shared__ float s[WIN_], red[256], q[128];
    const int h = blockIdx.x, t = threadIdx.x;
    const __nv_bfloat16* k = K + ((size_t)(h >> 1) * SK_ + (SK_ - WIN_)) * 128;
    const __nv_bfloat16* v = V + ((size_t)(h >> 1) * SK_ + (SK_ - WIN_)) * 128;
    if (t < 128) q[t] = fb_q[h * 128 + t];
    __syncthreads();
    float m = -INFINITY;
    for (int j = t; j < WIN_; j += 256) {
        float a = 0.f;
        for (int d = 0; d < 128; d++) a = fmaf(q[d], ldbf(k + (size_t)j * 128 + d), a);
        a = rbf(rbf(a) * 0.08838834764831845f);
        s[j] = a;
        m = fmaxf(m, a);
    }
    red[t] = m;
    __syncthreads();
    for (int o = 128; o > 0; o >>= 1) { if (t < o) red[t] = fmaxf(red[t], red[t + o]); __syncthreads(); }
    m = red[0];
    __syncthreads();
    float l = 0.f;
    for (int j = t; j < WIN_; j += 256) { s[j] = expf(s[j] - m); l += s[j]; }
    red[t] = l;
    __syncthreads();
    for (int o = 128; o > 0; o >>= 1) { if (t < o) red[t] += red[t + o]; __syncthreads(); }
    l = red[0];
    if (t < 128) {
        float a = 0.f;
        for (int j = 0; j < WIN_; j++) a = fmaf(rbf(s[j] / l), ldbf(v + (size_t)j * 128 + t), a);
        fb_o[h * 128 + t] = rbf(a);
    }
}
__global__ void fb_proj_kernel(const __nv_bfloat16* x, const __nv_bfloat16* wo) {
    const int n = blockIdx.x * blockDim.x + threadIdx.x;
    fb_x2[n] = rbf(ldbf(x + n) + rbf(fb_mod[2 * 576 + n] * gemv_fb(fb_o, wo, 4096, 576, n)));
}
__global__ void fb_w1_kernel(const __nv_bfloat16* w1) {
    __shared__ float h[576];
    ln_mod_fb(fb_x2, fb_mod + 4 * 576, fb_mod + 3 * 576, h);
    const int n = blockIdx.x * blockDim.x + threadIdx.x;
    fb_hv[n] = rbf(silu_fb(gemv_fb(h, w1, 576, F_, n)));
}
__global__ void fb_w2_kernel(const __nv_bfloat16* w2, __nv_bfloat16* out) {
    const int n = blockIdx.x * blockDim.x + threadIdx.x;
    out[n] = __float2bfloat16_rn(fb_x2[n] + rbf(fb_mod[5 * 576 + n] * gemv_fb(fb_hv, w2, F_, 576, n)));
}

typedef CUresult (*EncodeTiledFn)(CUtensorMap*, CUtensorMapDataType, cuuint32_t, void*, const cuuint64_t*, const cuuint64_t*,
                                  const cuuint32_t*, const cuuint32_t*, CUtensorMapInterleave, CUtensorMapSwizzle,
                                  CUtensorMapL2promotion, CUtensorMapFloatOOBfill);

bool encode2d(EncodeTiledFn enc, CUtensorMap* m, const void* ptr, uint64_t cols, uint64_t rows, uint32_t bc, uint32_t br,
              CUtensorMapSwizzle sw) {
    cuuint64_t dims[2] = {cols, rows};
    cuuint64_t str[1] = {cols * 2};
    cuuint32_t box[2] = {bc, br};
    cuuint32_t es[2] = {1, 1};
    return enc(m, CU_TENSOR_MAP_DATA_TYPE_BFLOAT16, 2, const_cast<void*>(ptr), dims, str, box, es, CU_TENSOR_MAP_INTERLEAVE_NONE,
               sw, CU_TENSOR_MAP_L2_PROMOTION_L2_128B, CU_TENSOR_MAP_FLOAT_OOB_FILL_NONE) == CUDA_SUCCESS;
}
bool encode_kv(EncodeTiledFn enc, CUtensorMap* m, const void* ptr) {
    cuuint64_t dims[3] = {64, 16ull * SK_, 2};
    cuuint64_t str[2] = {256, 128};
    cuuint32_t box[3] = {64, 32, 2};
    cuuint32_t es[3] = {1, 1, 1};
    return enc(m, CU_TENSOR_MAP_DATA_TYPE_BFLOAT16, 3, const_cast<void*>(ptr), dims, str, box, es, CU_TENSOR_MAP_INTERLEAVE_NONE,
               CU_TENSOR_MAP_SWIZZLE_128B, CU_TENSOR_MAP_L2_PROMOTION_L2_128B, CU_TENSOR_MAP_FLOAT_OOB_FILL_NONE) == CUDA_SUCCESS;
}

}

extern "C" void kernel_launch(void* const* d_in, const int* in_sizes, int n_in, void* d_out, int out_size) {
    (void)in_sizes; (void)n_in; (void)out_size;
    typedef const __nv_bfloat16* bfp;
    const cudaStream_t st = cudaStreamPerThread;
    cudaLaunchConfig_t cfg = {};
    cfg.gridDim = dim3(NCTA);
    cfg.blockDim = dim3(NTHREADS);
    cfg.dynamicSmemBytes = SMEM_BYTES;
    cfg.stream = st;
    cudaLaunchAttribute at[1];
    at[0].id = cudaLaunchAttributeClusterDimension;
    at[0].val.clusterDim.x = CL; at[0].val.clusterDim.y = 1; at[0].val.clusterDim.z = 1;
    cfg.attrs = at;
    cfg.numAttrs = 1;

    static EncodeTiledFn enc = nullptr;
    static int resident = -1;
    if (resident < 0) {
        void* fn = nullptr;
        cudaDriverEntryPointQueryResult qr;
        if (cudaGetDriverEntryPoint("cuTensorMapEncodeTiled", &fn, cudaEnableDefault, &qr) == cudaSuccess &&
            qr == cudaDriverEntryPointSuccess)
            enc = (EncodeTiledFn)fn;
        int ncl = 0;
        const bool ok = enc != nullptr &&
            cudaFuncSetAttribute(adaln_attn_mlp_decode_kernel, cudaFuncAttributeMaxDynamicSharedMemorySize, SMEM_BYTES) == cudaSuccess &&
            cudaOccupancyMaxActiveClusters(&ncl, adaln_attn_mlp_decode_kernel, &cfg) == cudaSuccess;
        resident = ok && ncl >= NCL;
        (void)cudaGetLastError();
    }

    Maps maps;
    const bool fast = resident &&
        encode2d(enc, &maps.wmod, d_in[9], 3456, 576, 40, 96, CU_TENSOR_MAP_SWIZZLE_NONE) &&
        encode2d(enc, &maps.wq, d_in[3], 4096, 576, 64, 48, CU_TENSOR_MAP_SWIZZLE_128B) &&
        encode_kv(enc, &maps.k, d_in[1]) && encode_kv(enc, &maps.v, d_in[2]) &&
        encode2d(enc, &maps.woa, d_in[4], 576, 4096, 64, 64, CU_TENSOR_MAP_SWIZZLE_128B) &&
        encode2d(enc, &maps.wob, d_in[4], 576, 4096, 32, 128, CU_TENSOR_MAP_SWIZZLE_64B) &&
        encode2d(enc, &maps.w1a, d_in[6], F_, 576, 64, 48, CU_TENSOR_MAP_SWIZZLE_128B) &&
        encode2d(enc, &maps.w1b, d_in[6], F_, 576, 32, 96, CU_TENSOR_MAP_SWIZZLE_64B) &&
        encode2d(enc, &maps.w2a, d_in[7], 576, F_, 64, 48, CU_TENSOR_MAP_SWIZZLE_128B) &&
        encode2d(enc, &maps.w2b, d_in[7], 576, F_, 32, 96, CU_TENSOR_MAP_SWIZZLE_64B);
    if (fast) {
        Ptrs p;
        p.x = (bfp)d_in[0];
        p.c = (bfp)d_in[8];
        p.out = (__nv_bfloat16*)d_out;
        cudaLaunchKernelEx(&cfg, adaln_attn_mlp_decode_kernel, maps, p);
        return;
    }
    fb_mod_kernel<<<27, 128, 0, st>>>((bfp)d_in[8], (bfp)d_in[9]);
    fb_q_kernel<<<32, 128, 0, st>>>((bfp)d_in[0], (bfp)d_in[3]);
    fb_attn_kernel<<<32, 256, 0, st>>>((bfp)d_in[1], (bfp)d_in[2]);
    fb_proj_kernel<<<9, 64, 0, st>>>((bfp)d_in[0], (bfp)d_in[4]);
    fb_w1_kernel<<<36, 128, 0, st>>>((bfp)d_in[6]);
    fb_w2_kernel<<<9, 64, 0, st>>>((bfp)d_in[7], (__nv_bfloat16*)d_out);
}
```
